```python
import torch

def _softmax(x, axis=-1):
    return torch.softmax(x, dim=axis)
def _gelu(x):
    return torch.nn.functional.gelu(x, approximate="tanh")
def _silu(x):
    return torch.nn.functional.silu(x)
def _sigmoid(x):
    return torch.sigmoid(x)
def _layernorm(x, axis=-1, eps=1e-5):
    m = x.mean(dim=axis, keepdim=True)
    v = x.var(dim=axis, keepdim=True, unbiased=False)
    return (x - m) / torch.sqrt(v + eps)
def _scatter_add(tgt, idx, src, axis=0):
    return tgt.clone().index_add_(axis, idx, src)
def _segment_sum(src, seg, n):
    out = torch.zeros((n,) + src.shape[1:], dtype=src.dtype)
    return out.index_add_(0, seg, src)
def _pad(x, pw):
    flat = tuple(v for pair in reversed(pw) for v in pair)
    return torch.nn.functional.pad(x, flat)

kernel_name = 'sequential_preLN__mha_block_cached__glu_gated_swiglu__decode'

def setup_inputs():

    _w = (lambda a: (lambda t: t.to(torch.bfloat16) if t.is_floating_point() else t)(torch.as_tensor(a)))
    def _A_setup():
        B, Sq, D = 4, 1, 512
        H, Sk, Dh = 32, 4096, 128
        return {
            "x": _w((lambda *s: torch.randn(*s, dtype=torch.bfloat16) * 0.05)(B, Sq, D)),
            "k_cache": _w((lambda *s: torch.randn(*s, dtype=torch.bfloat16) * 1.6)(B, H, Sk, Dh)),
            "v_cache": _w((lambda *s: torch.randn(*s, dtype=torch.bfloat16) * 0.8)(B, H, Sk, Dh)),
            "wq": _w((lambda *s: torch.randn(*s, dtype=torch.bfloat16) * 1.6)(D, H * Dh) * (D ** -0.5)),
            "wo": _w((lambda *s: torch.randn(*s, dtype=torch.bfloat16) * 0.8)(H * Dh, D) * ((H * Dh) ** -0.5)),
        }
    _A_in = _A_setup()

    def _B_setup():
        B, S, D, F = 4, 1, 512, 1792
        return {
            "x": _w((lambda *s: torch.randn(*s, dtype=torch.bfloat16) * 0.05)(B, S, D)),
            "w1": _w((lambda *s: torch.randn(*s, dtype=torch.bfloat16) * 0.4)(D, F) * (2.0 / D) ** 0.5),
            "w3": _w((lambda *s: torch.randn(*s, dtype=torch.bfloat16) * 0.4)(D, F) * (2.0 / D) ** 0.5),
            "w2": _w((lambda *s: torch.randn(*s, dtype=torch.bfloat16) * 0.4)(F, D) * (2.0 / F) ** 0.5),
        }
    _B_in = _B_setup()

    return {
        "A_x": _A_in["x"],
        "A_k_cache": _A_in["k_cache"],
        "A_v_cache": _A_in["v_cache"],
        "A_wq": _A_in["wq"],
        "A_wo": _A_in["wo"],
        "B_x": _B_in["x"],
        "B_w1": _B_in["w1"],
        "B_w3": _B_in["w3"],
        "B_w2": _B_in["w2"],
    }

def reference(A_x, A_k_cache, A_v_cache, A_wq, A_wo, B_x, B_w1, B_w3, B_w2):
    def _A_ref(x, k_cache, v_cache, wq, wo):
        B, Sq, D = x.shape
        H, Dh = 32, 128
        q = (lambda x, *d: x.permute(*d))((x @ wq).reshape(B, Sq, H, Dh), 0, 2, 1, 3)
        scores = torch.einsum("bhqd,bhkd->bhqk", q, k_cache) * (Dh ** -0.5)
        p = _softmax(scores, axis=-1)
        o = torch.einsum("bhqk,bhkd->bhqd", p, v_cache)
        return (lambda x, *d: x.permute(*d))(o, 0, 2, 1, 3).reshape(B, Sq, H * Dh) @ wo

    def _B_ref(x, w1, w3, w2):
        gate = torch.einsum("bsd,df->bsf", x, w1)
        up = torch.einsum("bsd,df->bsf", x, w3)
        h = _silu(gate) * up
        out = torch.einsum("bsf,fd->bsd", h, w2)
        return out

    x = A_x
    h = x + _A_ref(_layernorm(x, axis=-1), A_k_cache, A_v_cache, A_wq, A_wo)
    h2 = h + _B_ref(_layernorm(h, axis=-1), B_w1, B_w3, B_w2)
    return h2
```

```cpp
#include <cuda_runtime.h>
#include <cuda.h>
#include <cuda_bf16.h>
#include <stdint.h>

#define DEVINL __device__ __forceinline__

namespace fused {

constexpr int kD = 512, kF = 1792, kHD = 4096;
constexpr int kCtas = 128;
constexpr int kThreads = 576;
constexpr int kChunk = 16384;
constexpr int kStages = 5;
constexpr int kFfn1Ctas = 56;
constexpr int kFfn2First = 64;
constexpr int kFfn2Ctas = 32;
#define LOOKAHEAD 4
#define LA_END 128
#define WO_AT 16
#define WO_STEP 4
#define KFIRST 2
#define REP1 1
#define REP2 1
#define LL_NS 0
#define DRY_PASS 1
#define POLL_NS 0

constexpr int OFF_RING = 0;
constexpr int OFF_W = kStages * kChunk;
constexpr int kSPitch = 1040;
constexpr int OFF_S = OFF_W + 8 * kChunk;
constexpr int OFF_Q = OFF_S + 16 * kSPitch;
constexpr int OFF_X = OFF_Q + 256;
constexpr int OFF_STAT = OFF_X + 1024;
constexpr int OFF_HS = OFF_RING + (127 % kStages) * kChunk;
constexpr int OFF_PART = OFF_HS + 5632;
constexpr int OFF_BAR = OFF_STAT + 256;
constexpr int SMEM_BYTES = OFF_BAR + 8 * (16 + kStages + 8 + 3);
static_assert(SMEM_BYTES <= 232448 && LOOKAHEAD <= kStages, "smem");

constexpr uint32_t kSpinLimit = 1u << 22;

__device__ float2 g_acc[2][REP1][4 * kD];
__device__ uint4 g_ll[REP2][112 * 4 * 4];
__device__ unsigned g_epoch;
#define TS(i)
#define CT(p)
#define CK_(i, dep)

DEVINL uint32_t smem_u32(const void* p) { return (uint32_t)__cvta_generic_to_shared(p); }
DEVINL void mbar_init(uint32_t bar, uint32_t cnt) {
    asm volatile("mbarrier.init.shared::cta.b64 [%0], %1;" ::"r"(bar), "r"(cnt) : "memory");
}
DEVINL void mbar_expect_tx(uint32_t bar, uint32_t bytes) {
    asm volatile("mbarrier.arrive.expect_tx.shared::cta.b64 _, [%0], %1;" ::"r"(bar), "r"(bytes) : "memory");
}
DEVINL void mbar_arrive(uint32_t bar) {
    asm volatile("mbarrier.arrive.shared::cta.b64 _, [%0];" ::"r"(bar) : "memory");
}
DEVINL void mbar_wait(uint32_t bar, uint32_t parity) {
    uint32_t done, tries = 0;
    do {
        asm volatile(
            "{\n.reg .pred p;\nmbarrier.try_wait.parity.shared::cta.b64 p, [%1], %2;\nselp.u32 %0, 1, 0, p;\n}"
            : "=r"(done) : "r"(bar), "r"(parity) : "memory");
        if (!done && ++tries > kSpinLimit) __trap();
    } while (!done);
}
DEVINL void bulk_load_pol(uint32_t dst, const void* src, uint32_t bytes, uint32_t bar, uint64_t pol) {
    asm volatile("cp.async.bulk.shared::cluster.global.mbarrier::complete_tx::bytes.L2::cache_hint [%0], [%1], %2, [%3], %4;"
                 ::"r"(dst), "l"(src), "r"(bytes), "r"(bar), "l"(pol) : "memory");
}
DEVINL void tma_load_2d(uint32_t dst, const CUtensorMap* map, int c0, int c1, uint32_t bar) {
    asm volatile("cp.async.bulk.tensor.2d.shared::cluster.global.mbarrier::complete_tx::bytes [%0], [%1, {%3, %4}], [%2];"
                 ::"r"(dst), "l"(reinterpret_cast<uint64_t>(map)), "r"(bar), "r"(c0), "r"(c1) : "memory");
}
DEVINL void tmap_prefetch(const CUtensorMap* map) {
    asm volatile("prefetch.tensormap [%0];" ::"l"(reinterpret_cast<uint64_t>(map)) : "memory");
}
DEVINL void l2_prefetch(const void* src, uint32_t bytes) {
    asm volatile("cp.async.bulk.prefetch.L2.global [%0], %1;" ::"l"(src), "r"(bytes) : "memory");
}
DEVINL uint4 ldg_nc(const void* p) {
    uint4 v;
    asm volatile("ld.global.nc.v4.u32 {%0,%1,%2,%3}, [%4];"
                 : "=r"(v.x), "=r"(v.y), "=r"(v.z), "=r"(v.w) : "l"(p));
    return v;
}
DEVINL uint32_t ldg_nc32(const void* p) {
    uint32_t v;
    asm volatile("ld.global.nc.u32 %0, [%1];" : "=r"(v) : "l"(p));
    return v;
}
DEVINL void ldsm4(uint32_t (&r)[4], uint32_t addr) {
    asm volatile("ldmatrix.sync.aligned.m8n8.x4.shared.b16 {%0,%1,%2,%3}, [%4];"
                 : "=r"(r[0]), "=r"(r[1]), "=r"(r[2]), "=r"(r[3]) : "r"(addr) : "memory");
}
DEVINL void ldsm4t(uint32_t (&r)[4], uint32_t addr) {
    asm volatile("ldmatrix.sync.aligned.m8n8.x4.trans.shared.b16 {%0,%1,%2,%3}, [%4];"
                 : "=r"(r[0]), "=r"(r[1]), "=r"(r[2]), "=r"(r[3]) : "r"(addr) : "memory");
}
DEVINL void mma16816(float (&c)[4], const uint32_t (&a)[4], uint32_t b0, uint32_t b1) {
    asm volatile(
        "mma.sync.aligned.m16n8k16.row.col.f32.bf16.bf16.f32 {%0,%1,%2,%3}, {%4,%5,%6,%7}, {%8,%9}, {%0,%1,%2,%3};"
        : "+f"(c[0]), "+f"(c[1]), "+f"(c[2]), "+f"(c[3])
        : "r"(a[0]), "r"(a[1]), "r"(a[2]), "r"(a[3]), "r"(b0), "r"(b1));
}
DEVINL void bar_cons_() { asm volatile("bar.sync 1, 512;" ::: "memory"); }
#define bar_cons() do { if (live) bar_cons_(); } while (0)
DEVINL float bf16r(float v) { return __bfloat162float(__float2bfloat16_rn(v)); }
DEVINL float bf_lo(uint32_t u) { return __uint_as_float(u << 16); }
DEVINL float bf_hi(uint32_t u) { return __uint_as_float(u & 0xffff0000u); }
DEVINL uint32_t pack_bf16(float lo, float hi) {
    uint32_t r;
    asm("cvt.rn.bf16x2.f32 %0, %1, %2;" : "=r"(r) : "f"(hi), "f"(lo));
    return r;
}
DEVINL float warp_sum(float v) {
#pragma unroll
    for (int o = 16; o > 0; o >>= 1) v += __shfl_xor_sync(0xffffffffu, v, o);
    return v;
}
DEVINL float warp_max(float v) {
#pragma unroll
    for (int o = 16; o > 0; o >>= 1) v = fmaxf(v, __shfl_xor_sync(0xffffffffu, v, o));
    return v;
}
DEVINL float4 ld_relaxed_f4(const void* p) {
    float4 v;
    asm volatile("ld.relaxed.gpu.global.v4.f32 {%0,%1,%2,%3}, [%4];"
                 : "=f"(v.x), "=f"(v.y), "=f"(v.z), "=f"(v.w) : "l"(p) : "memory");
    return v;
}
DEVINL float2 ld_relaxed_f2(const void* p) {
    float2 v;
    asm volatile("ld.relaxed.gpu.global.v2.f32 {%0,%1}, [%2];" : "=f"(v.x), "=f"(v.y) : "l"(p) : "memory");
    return v;
}
DEVINL uint4 ld_relaxed_2x64(const void* p) {
    unsigned long long a, b;
    asm volatile("ld.relaxed.gpu.global.v2.b64 {%0,%1}, [%2];" : "=l"(a), "=l"(b) : "l"(p) : "memory");
    return make_uint4((uint32_t)a, (uint32_t)(a >> 32), (uint32_t)b, (uint32_t)(b >> 32));
}
DEVINL void st_relaxed_64(void* p, uint32_t lo, uint32_t hi) {
    unsigned long long v = (unsigned long long)lo | ((unsigned long long)hi << 32);
    asm volatile("st.relaxed.gpu.global.b64 [%0], %1;" ::"l"(p), "l"(v) : "memory");
}
DEVINL void red_add_f2(void* p, float a, float b) {
    asm volatile("red.relaxed.gpu.global.add.v2.f32 [%0], {%1,%2};" ::"l"(p), "f"(a), "f"(b) : "memory");
}
DEVINL int slot_at(int base, int r) {
    const int s = base % kStages + r;
    return s >= kStages ? s - kStages : s;
}

__global__ void __launch_bounds__(kThreads, 1)
fused_kernel(const __grid_constant__ CUtensorMap tm_wq, const __grid_constant__ CUtensorMap tm_wo,
             const __grid_constant__ CUtensorMap tm_w1, const __grid_constant__ CUtensorMap tm_w3,
             const __grid_constant__ CUtensorMap tm_w2,
             const __nv_bfloat16* __restrict__ x, const __nv_bfloat16* __restrict__ kc,
             const __nv_bfloat16* __restrict__ vc, const __nv_bfloat16* __restrict__ wo, const __nv_bfloat16* __restrict__ w1,
             const __nv_bfloat16* __restrict__ w3, const __nv_bfloat16* __restrict__ w2,
             __nv_bfloat16* __restrict__ out, const uint32_t zero) {
    extern __shared__ __align__(1024) unsigned char smem[];
    const uint32_t sb = smem_u32(smem);
    const int lane = threadIdx.x & 31;
    const bool live = threadIdx.x + zero < 544;
    const int tid = live ? threadIdx.x : lane, warp = tid >> 5;
    const int cta = blockIdx.x;
    const int b = cta >> 5, h = cta & 31;
    const uint32_t bar_full = sb + OFF_BAR, bar_empty = bar_full + 8 * 16, bar_wo = bar_empty + 8 * kStages,
                   bar_ffn = bar_wo + 8 * 8, bar_x = bar_ffn + 8, bar_wfree = bar_x + 8;
    const int role = (cta < kFfn1Ctas) ? 1 : ((cta >= kFfn2First && cta < kFfn2First + kFfn2Ctas) ? 2 : 0);

    if (threadIdx.x == 512) {
        tmap_prefetch(&tm_wq);
#pragma unroll
        for (int s = 0; s < 16; s++) mbar_init(bar_full + 8 * s, 1);
#pragma unroll
        for (int s = 0; s < kStages; s++) mbar_init(bar_empty + 8 * s, 4);
#pragma unroll
        for (int s = 0; s < 10; s++) mbar_init(bar_wo + 8 * s, 1);
        mbar_init(bar_wfree, 16);
        asm volatile("fence.mbarrier_init.release.cluster;" ::: "memory");
        asm volatile("fence.proxy.async.shared::cta;" ::: "memory");
        mbar_expect_tx(bar_x, 1024);
        asm volatile("cp.async.bulk.shared::cluster.global.mbarrier::complete_tx::bytes [%0], [%1], %2, [%3];"
                     ::"r"(sb + OFF_X), "l"(x + b * kD), "r"(1024), "r"(bar_x) : "memory");
    }
    __syncthreads();
    if (threadIdx.x >= 512) {
        if (lane == 0) {
            const char* kbase = reinterpret_cast<const char*>(kc) + (size_t)cta * (64 * kChunk);
            const char* vbase = reinterpret_cast<const char*>(vc) + (size_t)cta * (64 * kChunk);
            uint64_t pol;
            asm volatile("createpolicy.fractional.L2::evict_first.b64 %0, 1.0;" : "=l"(pol));
            int slot = 0;
            int wslot = 0, waited = -kStages;
            uint32_t wphase = 1;
            const int n_steps = live ? (role ? 132 : 128) : 4;
#pragma unroll 1
            for (int step = 0; step < n_steps; step++) {
                constexpr unsigned kDryList = (KFIRST - 1) | WO_AT << 8 | 128u << 16 | 130u << 24;
                const int c = live ? step : (int)((kDryList >> (8 * step)) & 255);
                const int la = (c < kStages || c >= LA_END) ? kStages : LOOKAHEAD;
                while (live && waited <= c - la) {
                    mbar_wait(bar_empty + 8 * wslot, wphase);
                    waited++;
                    if (++wslot == kStages) { wslot = 0; wphase ^= 1; }
                }
                const uint32_t dst = sb + OFF_RING + slot * kChunk;
                if (c < 128) {
                    const char* src = (c < 64) ? kbase + (size_t)c * kChunk : vbase + (size_t)(c - 64) * kChunk;
                    if (live) {
                        mbar_expect_tx(bar_full + 8 * ((c + 8) & 15), kChunk);
                        bulk_load_pol(dst, src, kChunk, bar_full + 8 * ((c + 8) & 15), pol);
                    }
                    if (c == KFIRST - 1) {
#pragma unroll 1
                        for (int k = 0; k < (live ? 8 : 1); k++) {
                            if (live) {
                                mbar_expect_tx(bar_full + 8 * k, kChunk);
                                tma_load_2d(sb + OFF_W + k * kChunk, &tm_wq, h * 128, k * 64, bar_full + 8 * k);
                            }
                        }
                        tmap_prefetch(&tm_wo);
                        if (role == 1) { tmap_prefetch(&tm_w1); tmap_prefetch(&tm_w3); }
                        if (role == 2) tmap_prefetch(&tm_w2);
                    }
                    const int k = (c - WO_AT) / WO_STEP;
                    if (c >= WO_AT && k < 8 && c == WO_AT + k * WO_STEP) {
                        if (live) {
                            if (k == 0) mbar_wait(bar_wfree, 0);
                            mbar_expect_tx(bar_wo + 8 * k, kChunk);
                            tma_load_2d(sb + OFF_W + k * kChunk, &tm_wo, k * 64, h * 128, bar_wo + 8 * k);
                        }
                    }
                } else {
                    const int k = c - 128;
                    if (role == 1) {
                        if (k == 0 && live) mbar_expect_tx(bar_ffn, 4 * kChunk);
                        if (live) tma_load_2d(dst, (k & 2) ? &tm_w3 : &tm_w1, cta * 32, (k & 1) * 256, bar_ffn);
                    } else {
                        if (k == 0 && live) mbar_expect_tx(bar_ffn, 7 * 8192);
                        if (live) tma_load_2d(dst, &tm_w2, (cta - kFfn2First) * 16, k * 512, bar_ffn);
                        if (k < 3 && live) tma_load_2d(dst + 8192, &tm_w2, (cta - kFfn2First) * 16, k * 512 + 256, bar_ffn);
                    }
                }
                if (++slot == kStages) slot = 0;
            }
        }
        if (live) return;
        __syncwarp();
    }

    TS(0);
    const int g = lane >> 2, t = lane & 3;
    const int set = warp >> 2;
    const int grp = warp & 3;
    uint32_t mask[8];
    {
        const int dd = (g - 2 * t) & 7;
#pragma unroll
        for (int j = 0; j < 8; j++)
            mask[j] = (j == dd ? 0x0000ffffu : 0u) | (j == ((dd - 1) & 7) ? 0xffff0000u : 0u);
    }
    const uint32_t vrow = sb + OFF_RING + grp * 4096 + ((lane & 7) + (lane >> 4) * 8) * 256 + ((lane >> 3) & 1) * 128;
    const uint32_t krow = sb + OFF_RING + grp * 4096 + ((lane & 7) + ((lane >> 3) & 1) * 8) * 256 + (lane >> 4) * 128;
    unsigned char* const srow = smem + OFF_S + warp * kSPitch;
    const bool diag = (t == (g >> 1));
    const bool godd = (g & 1) != 0;

    if (!DRY_PASS && !live) return;
    const int nit = live ? 16 : 1;
    unsigned epoch = 0;
    if (live) asm volatile("ld.relaxed.gpu.global.u32 %0, [%1];" : "=r"(epoch) : "l"(&g_epoch) : "memory");
    {
        if (live) mbar_wait(bar_x, 0);
        const uint4 xa = reinterpret_cast<const uint4*>(smem + OFF_X)[2 * lane];
        const uint4 xb = reinterpret_cast<const uint4*>(smem + OFF_X)[2 * lane + 1];
        float xv[16];
        xv[0] = bf_lo(xa.x); xv[1] = bf_hi(xa.x); xv[2] = bf_lo(xa.y); xv[3] = bf_hi(xa.y);
        xv[4] = bf_lo(xa.z); xv[5] = bf_hi(xa.z); xv[6] = bf_lo(xa.w); xv[7] = bf_hi(xa.w);
        xv[8] = bf_lo(xb.x); xv[9] = bf_hi(xb.x); xv[10] = bf_lo(xb.y); xv[11] = bf_hi(xb.y);
        xv[12] = bf_lo(xb.z); xv[13] = bf_hi(xb.z); xv[14] = bf_lo(xb.w); xv[15] = bf_hi(xb.w);
        float s = 0.f;
#pragma unroll
        for (int i = 0; i < 16; i++) s += xv[i];
        const float mean = warp_sum(s) * (1.f / kD);
        float v = 0.f;
#pragma unroll
        for (int i = 0; i < 16; i++) { const float d = xv[i] - mean; v += d * d; }
        const float var = warp_sum(v) * (1.f / kD);
        const float den = bf16r(sqrtf(bf16r(bf16r(var) + 1e-5f)));
        const float mb = bf16r(mean);
        uint32_t xn[4];
#pragma unroll
        for (int k = 0; k < 4; k++) {
            const uint32_t u = reinterpret_cast<const uint32_t*>(smem + OFF_X)[(set + 4 * (k >> 1)) * 32 + grp * 8 + t + (k & 1) * 4];
            xn[k] = pack_bf16(bf16r(bf_lo(u) - mb) / den, bf16r(bf_hi(u) - mb) / den);
        }
        TS(8);
        float c0[4] = {0.f, 0.f, 0.f, 0.f}, c1[4] = {0.f, 0.f, 0.f, 0.f};
#pragma unroll 1
        for (int k = 0; k < 2; k++) {
            const int sl = 4 * k + set;
            const uint32_t pp0 = k ? xn[2] : xn[0], pp1 = k ? xn[3] : xn[1];
            if (live) mbar_wait(bar_full + 8 * sl, 0);
            CT(sl);
#pragma unroll
            for (int j = 0; j < 8; j += 2) {
                uint32_t a0[4], a1[4];
                ldsm4t(a0, vrow + OFF_W + sl * kChunk + ((lane + j) & 7) * 16);
                ldsm4t(a1, vrow + OFF_W + sl * kChunk + ((lane + j + 1) & 7) * 16);
                mma16816(c0, a0, pp0 & mask[j], pp1 & mask[j]);
                mma16816(c1, a1, pp0 & mask[j + 1], pp1 & mask[j + 1]);
            }
        }
        if (lane == 0 && live) mbar_arrive(bar_wfree + ((__float_as_uint(c0[0]) ^ __float_as_uint(c1[0])) & zero));
        TS(9);
        float* qp = reinterpret_cast<float*>(srow);
        if (live) {
            qp[(2 * t) * 8 + g] = c0[0] + c1[0];
            qp[(2 * t + 1) * 8 + g] = c0[1] + c1[1];
            qp[(2 * t + 8) * 8 + g] = c0[2] + c1[2];
            qp[(2 * t + 9) * 8 + g] = c0[3] + c1[3];
        }
        bar_cons();
        if (tid < 128) {
            const float* qs = reinterpret_cast<const float*>(smem + OFF_S) + tid;
            float q = 0.f;
#pragma unroll
            for (int w = 0; w < 16; w++) q += qs[w * (kSPitch / 4)];
            if (live) reinterpret_cast<__nv_bfloat16*>(smem + OFF_Q)[tid] = __float2bfloat16_rn(q);
        }
        bar_cons();
    }
    int sl = set;
    {
        uint32_t bq0[8], bq1[8];
        const uint32_t* q2 = reinterpret_cast<const uint32_t*>(smem + OFF_Q);
#pragma unroll
        for (int j = 0; j < 8; j++) {
            bq0[j] = q2[((g + j) & 7) * 4 + t];
            bq1[j] = q2[32 + ((g + j) & 7) * 4 + t];
        }
        TS(1);
        float* sc = reinterpret_cast<float*>(srow);
        float mx = -INFINITY;
#pragma unroll 1
        for (int it = 0; it < nit; it++) {
            const int n = it + 2;
            if (live) mbar_wait(bar_full + 8 * ((n & 3) * 4 + set), (n >> 2) & 1);
            CT(4 * n + set);
            float c0[4] = {0.f, 0.f, 0.f, 0.f}, c1[4] = {0.f, 0.f, 0.f, 0.f};
#pragma unroll
            for (int j = 0; j < 8; j += 2) {
                uint32_t a0[4], a1[4];
                ldsm4(a0, krow + sl * kChunk + ((lane + j) & 7) * 16);
                ldsm4(a1, krow + sl * kChunk + ((lane + j + 1) & 7) * 16);
                mma16816(c0, a0, bq0[j], bq1[j]);
                mma16816(c1, a1, bq0[j + 1], bq1[j + 1]);
            }
            if (lane == 0 && live) mbar_arrive(bar_empty + 8 * sl + ((__float_as_uint(c0[0]) ^ __float_as_uint(c1[0])) & zero));
            const float slo = godd ? c0[1] + c1[1] : c0[0] + c1[0];
            const float shi = godd ? c0[3] + c1[3] : c0[2] + c1[2];
            if (diag && live) {
                sc[it * 16 + g] = slo;
                sc[it * 16 + g + 8] = shi;
                mx = fmaxf(mx, fmaxf(slo, shi));
            }
            sl += 4;
            if (sl >= kStages) sl -= kStages;
        }
        TS(2);
        float* smax = reinterpret_cast<float*>(smem + OFF_STAT);
        float* ssum = smax + 16;
        mx = warp_max(mx);
        if (lane == 0 && live) smax[warp] = mx;
        bar_cons();
        {
            const float4* p4 = reinterpret_cast<const float4*>(smax);
            const float4 m0 = p4[0], m1 = p4[1], m2 = p4[2], m3 = p4[3];
            mx = fmaxf(fmaxf(fmaxf(m0.x, m0.y), fmaxf(m0.z, m0.w)), fmaxf(fmaxf(m1.x, m1.y), fmaxf(m1.z, m1.w)));
            mx = fmaxf(mx, fmaxf(fmaxf(fmaxf(m2.x, m2.y), fmaxf(m2.z, m2.w)), fmaxf(fmaxf(m3.x, m3.y), fmaxf(m3.z, m3.w))));
        }
        const float cs = 0.08838834764831845f * 1.4426950408889634f;
        const float4 s0 = reinterpret_cast<const float4*>(sc)[2 * lane], s1 = reinterpret_cast<const float4*>(sc)[2 * lane + 1];
        float e[8] = {s0.x, s0.y, s0.z, s0.w, s1.x, s1.y, s1.z, s1.w};
        float sum = 0.f;
#pragma unroll
        for (int i = 0; i < 8; i++) { e[i] = exp2f((e[i] - mx) * cs); sum += e[i]; }
        sum = warp_sum(sum);
        if (lane == 0 && live) ssum[warp] = sum;
        bar_cons();
        {
            const float4* p4 = reinterpret_cast<const float4*>(ssum);
            const float4 m0 = p4[0], m1 = p4[1], m2 = p4[2], m3 = p4[3];
            sum = ((m0.x + m0.y) + (m0.z + m0.w)) + ((m1.x + m1.y) + (m1.z + m1.w)) +
                  ((m2.x + m2.y) + (m2.z + m2.w)) + ((m3.x + m3.y) + (m3.z + m3.w));
        }
        const float inv = 1.f / sum;
        if (live) reinterpret_cast<uint4*>(srow + 512)[lane] =
            make_uint4(pack_bf16(e[0] * inv, e[1] * inv), pack_bf16(e[2] * inv, e[3] * inv),
                       pack_bf16(e[4] * inv, e[5] * inv), pack_bf16(e[6] * inv, e[7] * inv));
        __syncwarp();
    }
    const int par = epoch & 1;
    const unsigned tag = epoch + 1;
    if (live) {
        if (tid < 16 * REP1) g_acc[par ^ 1][tid >> 4][cta * 16 + (tid & 15)] = make_float2(0.f, 0.f);
    }
    float oc[4];
    {
        const uint32_t* pw = reinterpret_cast<const uint32_t*>(srow + 512) + t;
        float c0[4] = {0.f, 0.f, 0.f, 0.f}, c1[4] = {0.f, 0.f, 0.f, 0.f};
#pragma unroll 1
        for (int it = 0; it < nit; it++) {
            const int n = it + 18;
            const uint32_t pp0 = pw[it * 8], pp1 = pw[it * 8 + 4];
            if (live) mbar_wait(bar_full + 8 * ((n & 3) * 4 + set), (n >> 2) & 1);
            CT(4 * n + set);
            CK_(0, 0);
#pragma unroll
            for (int j = 0; j < 8; j += 2) {
                uint32_t a0[4], a1[4];
                ldsm4t(a0, vrow + sl * kChunk + ((lane + j) & 7) * 16);
                ldsm4t(a1, vrow + sl * kChunk + ((lane + j + 1) & 7) * 16);
                mma16816(c0, a0, pp0 & mask[j], pp1 & mask[j]);
                mma16816(c1, a1, pp0 & mask[j + 1], pp1 & mask[j + 1]);
            }
            if (lane == 0 && live) mbar_arrive(bar_empty + 8 * sl + ((__float_as_uint(c0[0]) ^ __float_as_uint(c1[0])) & zero));
            sl += 4;
            if (sl >= kStages) sl -= kStages;
        }
#pragma unroll
        for (int k = 0; k < 4; k++) oc[k] = c0[k] + c1[k];
    }
    TS(3);
    CK_(1, __float_as_uint(oc[0]) + __float_as_uint(oc[3]));
    {
        if (warp >= 8) {
            if (live) {
                reinterpret_cast<float4*>(srow)[lane] = make_float4(oc[0], oc[1], oc[2], oc[3]);
                asm volatile("bar.arrive %0, 64;" ::"r"(2 + (warp & 7)) : "memory");
            }
        }
        uint32_t wf[8][2][4];
        {
            const int k = warp >> 1;
            if (live) mbar_wait(bar_wo + 8 * k, 0);
            const int r8 = lane & 7;
            const uint32_t base = sb + OFF_W + k * kChunk + (r8 + (lane >> 4) * 8) * 128;
            const int cu = (warp & 1) * 4 + ((lane >> 3) & 1);
#pragma unroll
            for (int s = 0; s < 8; s++) {
                ldsm4t(wf[s][0], base + s * 2048 + ((cu ^ r8) * 16));
                ldsm4t(wf[s][1], base + s * 2048 + (((cu + 2) ^ r8) * 16));
            }
        }
        if (warp < 8) {
            if (live) asm volatile("bar.sync %0, 64;" ::"r"(2 + warp) : "memory");
            const float4 o2 = reinterpret_cast<const float4*>(srow + 8 * kSPitch)[lane];
            __nv_bfloat16* op = reinterpret_cast<__nv_bfloat16*>(srow);
            if (live) {
                op[(2 * t) * 8 + g] = __float2bfloat16_rn(oc[0] + o2.x);
                op[(2 * t + 1) * 8 + g] = __float2bfloat16_rn(oc[1] + o2.y);
                op[(2 * t + 8) * 8 + g] = __float2bfloat16_rn(oc[2] + o2.z);
                op[(2 * t + 9) * 8 + g] = __float2bfloat16_rn(oc[3] + o2.w);
            }
        }
        CK_(2, wf[7][1][3] + wf[0][0][0]);
        bar_cons();
        float acc[4][4];
#pragma unroll
        for (int a = 0; a < 4; a++)
#pragma unroll
            for (int k = 0; k < 4; k++) acc[a][k] = 0.f;
        const uint32_t brow = sb + OFF_S + (lane & 7) * kSPitch + (lane >> 3) * 16;
#pragma unroll
        for (int s2 = 0; s2 < 4; s2++) {
            uint32_t bA[4];
            ldsm4(bA, brow + s2 * 64);
            if (s2 == 0) CK_(3, bA[0]);
            mma16816(acc[0], wf[s2 * 2][0], bA[0], bA[1]);
            mma16816(acc[2], wf[s2 * 2][1], bA[0], bA[1]);
            mma16816(acc[1], wf[s2 * 2 + 1][0], bA[2], bA[3]);
            mma16816(acc[3], wf[s2 * 2 + 1][1], bA[2], bA[3]);
        }
        const float v0 = (acc[0][0] + acc[0][1]) + (acc[1][0] + acc[1][1]);
        const float v1 = (acc[0][2] + acc[0][3]) + (acc[1][2] + acc[1][3]);
        const float v2 = (acc[2][0] + acc[2][1]) + (acc[3][0] + acc[3][1]);
        const float v3 = (acc[2][2] + acc[2][3]) + (acc[3][2] + acc[3][3]);
        CK_(4, __float_as_uint(v0 + v1 + v2 + v3));
        const bool o1 = (t & 1) != 0, o2 = (t & 2) != 0;
        const float ra = (o1 ? v1 : v0) + __shfl_xor_sync(0xffffffffu, o1 ? v0 : v1, 1);
        const float rb = (o1 ? v3 : v2) + __shfl_xor_sync(0xffffffffu, o1 ? v2 : v3, 1);
        const float r = (o2 ? rb : ra) + __shfl_xor_sync(0xffffffffu, o2 ? ra : rb, 2);
        if (live) {
#pragma unroll
            for (int rp = 0; rp < REP1; rp++)
                red_add_f2(&g_acc[par][rp][b * kD + warp * 32 + (t >> 1) * 16 + (t & 1) * 8 + g], r, 1.0f);
        }
    }
    CK_(5, 0);
    TS(4);
    if (role == 0) return;

    uint32_t af[8][4];
    if (live) mbar_wait(bar_ffn, 0);
    TS(10);
    {
        const int rr = (lane & 7) + (lane >> 4) * 8, c = (lane >> 3) & 1;
        if (role == 1) {
            const int kq = warp >> 2;
            const uint32_t box = sb + OFF_RING + slot_at(128, (warp & 2) + (kq >> 1)) * kChunk;
#pragma unroll
            for (int s = 0; s < 8; s++) {
                const int r = (kq & 1) * 128 + s * 16 + rr;
                ldsm4t(af[s], box + r * 64 + ((((warp & 1) * 2 + c) ^ ((r >> 1) & 3)) * 16));
            }
        } else {
#pragma unroll
            for (int s = 0; s < 7; s++) {
                const int f = warp * 112 + s * 16 + rr;
                const uint32_t box = sb + OFF_RING + slot_at(128, f >> 9) * kChunk;
                ldsm4t(af[s], box + (f & 511) * 32 + ((c ^ ((f >> 2) & 1)) * 16));
            }
        }
    }
    constexpr uint32_t off_hs = OFF_HS, off_part = OFF_PART;
    float* part = reinterpret_cast<float*>(smem + off_part);

    if (role == 1) {
        const int bb = tid >> 7, c4 = (tid & 127) * 4;
        uint2 xr = make_uint2(0u, 0u);
        if (live) asm volatile("ld.global.nc.v2.u32 {%0,%1}, [%2];" : "=r"(xr.x), "=r"(xr.y) : "l"(x + bb * kD + c4));
        if (tid < 64 && live) reinterpret_cast<uint4*>(smem + off_hs + 4 * 1040)[tid] = make_uint4(0x3f803f80u, 0x3f803f80u, 0x3f803f80u, 0x3f803f80u);
        const float4* src = reinterpret_cast<const float4*>(&g_acc[par][cta % REP1][bb * kD + c4]);
        float4 u0 = make_float4(0.f, 0.f, 0.f, 0.f), u1 = u0;
        uint32_t tries = 0;
        while (live) {
            u0 = ld_relaxed_f4(src);
            u1 = ld_relaxed_f4(src + 1);
            if (u0.y == 32.f && u0.w == 32.f && u1.y == 32.f && u1.w == 32.f) break;
            if (++tries > kSpinLimit) __trap();
            if (POLL_NS) __nanosleep(POLL_NS);
        }
        CK_(6, __float_as_uint(u0.x));
        const uint32_t x0 = xr.x, x1 = xr.y;
        const float h0 = bf16r(bf_lo(x0) + bf16r(u0.x)), h1 = bf16r(bf_hi(x0) + bf16r(u0.z));
        const float h2 = bf16r(bf_lo(x1) + bf16r(u1.x)), h3 = bf16r(bf_hi(x1) + bf16r(u1.z));
        if (live) *reinterpret_cast<uint2*>(smem + off_hs + bb * 1040 + c4 * 2) = make_uint2(pack_bf16(h0, h1), pack_bf16(h2, h3));
        bar_cons();
        const int kq = warp >> 2;
        float c0[4] = {0.f, 0.f, 0.f, 0.f}, c1[4] = {0.f, 0.f, 0.f, 0.f};
        float q0[4] = {0.f, 0.f, 0.f, 0.f}, q1[4] = {0.f, 0.f, 0.f, 0.f};
        const uint32_t brow = sb + off_hs + min(lane & 7, 4) * 1040 + (kq * 128 + (lane >> 3) * 8) * 2;
        const bool statw = (warp & 3) == 0;
#pragma unroll
        for (int s2 = 0; s2 < 4; s2++) {
            uint32_t bf[4];
            ldsm4(bf, brow + s2 * 64);
            if (s2 == 0) CK_(7, bf[0]);
            mma16816(c0, af[2 * s2], bf[0], bf[1]);
            mma16816(c1, af[2 * s2 + 1], bf[2], bf[3]);
            if (statw) {
                const uint32_t a0[4] = {bf[0], 0u, bf[1], 0u}, a1[4] = {bf[2], 0u, bf[3], 0u};
                mma16816(q0, a0, bf[0], bf[1]);
                mma16816(q1, a1, bf[2], bf[3]);
            }
        }
        CK_(8, __float_as_uint(c0[0] + c1[0]));
        TS(5);
        if (t < 3 && live) {
            float* pw = part + ((warp & 3) * 16 + g) * 28 + t * 8 + kq;
            pw[0] = c0[0] + c1[0]; pw[4] = c0[1] + c1[1];
            pw[224] = c0[2] + c1[2]; pw[228] = c0[3] + c1[3];
            if (statw) { float* ps = part + (64 + g) * 28 + t * 8 + kq; ps[0] = q0[0] + q1[0]; ps[4] = q0[1] + q1[1]; }
        }
        bar_cons();
        if (tid < 128) {
            const int eb = tid & 3, fl = tid >> 2, tile = fl >> 4, m = fl & 15;
            const float4* p4 = reinterpret_cast<const float4*>(part);
            const float4 vg = p4[(tile * 16 + m) * 7 + eb], vgs = p4[(tile * 16 + m) * 7 + 4];
            const float4 vu = p4[((tile + 2) * 16 + m) * 7 + eb], vus = p4[((tile + 2) * 16 + m) * 7 + 4];
            const float4 vq = p4[(64 + eb) * 7 + eb], vs = p4[(64 + 4) * 7 + eb];
            const float gr = (vg.x + vg.y) + (vg.z + vg.w), gs = (vgs.x + vgs.y) + (vgs.z + vgs.w);
            const float ur = (vu.x + vu.y) + (vu.z + vu.w), us = (vus.x + vus.y) + (vus.z + vus.w);
            CK_(10, __float_as_uint(gr + us));
            const float mean = ((vs.x + vs.y) + (vs.z + vs.w)) * (1.f / kD);
            const float var = fmaxf(((vq.x + vq.y) + (vq.z + vq.w)) * (1.f / kD) - mean * mean, 0.f);
            float sq, rden;
            asm("sqrt.approx.f32 %0, %1;" : "=f"(sq) : "f"(bf16r(bf16r(var) + 1e-5f)));
            asm("rcp.approx.f32 %0, %1;" : "=f"(rden) : "f"(bf16r(sq)));
            const float mb = bf16r(mean);
            const float gate = bf16r((gr - mb * gs) * rden);
            const float up = bf16r((ur - mb * us) * rden);
            const float act = bf16r(__fdividef(gate, 1.f + __expf(-gate)));
            const float hh = bf16r(act * up);
            CK_(11, __float_as_uint(hh));
            const float hn = __shfl_xor_sync(0xffffffffu, hh, 4);
            if ((fl & 1) == 0 && live) {
                const int ks = cta * 2 + tile;
                const uint32_t pk = pack_bf16(hh, hn);
#pragma unroll
                for (int rp = 0; rp < REP2; rp++)
                    st_relaxed_64(reinterpret_cast<char*>(&g_ll[rp][(ks * 4 + eb) * 4 + ((m & 7) >> 1)]) + (m >> 3) * 8, pk, tag);
            }
        }
        CK_(12, 0);
        TS(6);
    } else {
        const int c0col = (cta - kFfn2First) * 16;
        float hres = 0.f;
        const int oo = tid >> 2, om = oo >> 2, ob = oo & 3;
        if (tid < 256 && (tid & 3) == 0 && live) {
            const float xv = __bfloat162float(x[ob * kD + c0col + om]);
            float2 u;
            uint32_t tries = 0;
            while (true) {
                u = ld_relaxed_f2(&g_acc[par][cta % REP1][ob * kD + c0col + om]);
                if (u.y == 32.f) break;
                if (++tries > kSpinLimit) __trap();
                if (POLL_NS) __nanosleep(POLL_NS);
            }
            hres = bf16r(xv + bf16r(u.x));
        }
        TS(11);
        uint4 ll[7];
#pragma unroll
        for (int s = 0; s < 7; s++) ll[s] = make_uint4(0u, 0u, 0u, 0u);
        const uint4* lsrc = &g_ll[cta % REP2][(warp * 7 * 4 + (g & 3)) * 4 + t];
        uint32_t tries = 0;
        while (live) {
            bool ok = true;
#pragma unroll
            for (int s = 0; s < 7; s++) ll[s] = ld_relaxed_2x64(lsrc + s * 16);
#pragma unroll
            for (int s = 0; s < 7; s++) ok = ok && (ll[s].y == tag) && (ll[s].w == tag);
            if (__all_sync(0xffffffffu, ok)) break;
            if (++tries > kSpinLimit) __trap();
            if (LL_NS) __nanosleep(LL_NS);
        }
        CK_(6, ll[0].x);
        TS(12);
        float c0[4] = {0.f, 0.f, 0.f, 0.f}, c1[4] = {0.f, 0.f, 0.f, 0.f};
#pragma unroll
        for (int s = 0; s < 7; s++) {
            if (s & 1) mma16816(c1, af[s], ll[s].x, ll[s].z);
            else mma16816(c0, af[s], ll[s].x, ll[s].z);
        }
        CK_(7, __float_as_uint(c0[0] + c1[0]));
        if (t < 2 && live) {
            float* pw = part + (g * 4 + 2 * t) * 16 + warp;
            pw[0] = c0[0] + c1[0]; pw[16] = c0[1] + c1[1];
            pw[512] = c0[2] + c1[2]; pw[528] = c0[3] + c1[3];
        }
        bar_cons();
        if (tid < 256) {
            const int qq = tid & 3;
            const float4 pv = reinterpret_cast<const float4*>(part)[tid];
            float s = (pv.x + pv.y) + (pv.z + pv.w);
            CK_(8, __float_as_uint(s));
            s += __shfl_xor_sync(0xffffffffu, s, 1);
            s += __shfl_xor_sync(0xffffffffu, s, 2);
            if (qq == 0 && live) out[ob * kD + c0col + om] = __float2bfloat16_rn(hres + bf16r(s));
        }
        if (cta == kFfn2First && tid == 0 && live) g_epoch = epoch + 1;
        CK_(9, 0);
        TS(7);
    }
}

typedef CUresult (*EncodeFn)(CUtensorMap*, CUtensorMapDataType, cuuint32_t, void*, const cuuint64_t*, const cuuint64_t*,
                             const cuuint32_t*, const cuuint32_t*, CUtensorMapInterleave, CUtensorMapSwizzle,
                             CUtensorMapL2promotion, CUtensorMapFloatOOBfill);

static void make_map(EncodeFn enc, CUtensorMap* m, void* ptr, uint64_t cols, uint64_t rows, uint32_t bc, uint32_t br,
                     CUtensorMapSwizzle sw) {
    cuuint64_t dims[2] = {cols, rows};
    cuuint64_t strides[1] = {cols * 2};
    cuuint32_t box[2] = {bc, br};
    cuuint32_t es[2] = {1, 1};
    enc(m, CU_TENSOR_MAP_DATA_TYPE_BFLOAT16, 2, ptr, dims, strides, box, es, CU_TENSOR_MAP_INTERLEAVE_NONE, sw,
        CU_TENSOR_MAP_L2_PROMOTION_L2_128B, CU_TENSOR_MAP_FLOAT_OOB_FILL_NONE);
}

}

extern "C" void kernel_launch(void* const* d_in, const int* in_sizes, int n_in, void* d_out, int out_size) {
    (void)in_sizes; (void)n_in; (void)out_size;
    using namespace fused;
    static EncodeFn enc = nullptr;
    if (!enc) {
        void* fn = nullptr;
        cudaDriverEntryPointQueryResult st;
        cudaGetDriverEntryPoint("cuTensorMapEncodeTiled", &fn, cudaEnableDefault, &st);
        enc = (EncodeFn)fn;
        cudaFuncSetAttribute(fused_kernel, cudaFuncAttributeMaxDynamicSharedMemorySize, SMEM_BYTES);
    }
    CUtensorMap mq, mo, m1, m3, m2;
    make_map(enc, &mq, d_in[3], kHD, kD, 128, 64, CU_TENSOR_MAP_SWIZZLE_NONE);
    make_map(enc, &mo, d_in[4], kD, kHD, 64, 128, CU_TENSOR_MAP_SWIZZLE_128B);
    make_map(enc, &m1, d_in[6], kF, kD, 32, 256, CU_TENSOR_MAP_SWIZZLE_64B);
    make_map(enc, &m3, d_in[7], kF, kD, 32, 256, CU_TENSOR_MAP_SWIZZLE_64B);
    make_map(enc, &m2, d_in[8], kD, kF, 16, 256, CU_TENSOR_MAP_SWIZZLE_32B);
    fused_kernel<<<kCtas, kThreads, SMEM_BYTES>>>(
        mq, mo, m1, m3, m2, (const __nv_bfloat16*)d_in[0], (const __nv_bfloat16*)d_in[1], (const __nv_bfloat16*)d_in[2],
        (const __nv_bfloat16*)d_in[4], (const __nv_bfloat16*)d_in[6], (const __nv_bfloat16*)d_in[7], (const __nv_bfloat16*)d_in[8],
        (__nv_bfloat16*)d_out, 0u);
}
```

```cpp
#include <cuda_runtime.h>
#include <cuda.h>
#include <cuda_bf16.h>
#include <stdint.h>

#define DEVINL __device__ __forceinline__

namespace fused {

constexpr int kD = 512, kF = 1792, kHD = 4096;
constexpr int kCtas = 128;
constexpr int kThreads = 576;
constexpr int kChunk = 16384;
constexpr int kStages = 5;
constexpr int kLookahead = 4;
constexpr int kWoAt = 16, kWoStep = 4;
constexpr int kWfPre = 6;
constexpr int kFfn1Ctas = 56;
constexpr int kFfn2First = 64;
constexpr int kFfn2Ctas = 32;

constexpr int OFF_RING = 0;
constexpr int OFF_W = kStages * kChunk;
constexpr int kSPitch = 1040;
constexpr int OFF_S = OFF_W + 8 * kChunk;
constexpr int OFF_Q = OFF_S + 16 * kSPitch;
constexpr int OFF_X = OFF_Q + 256;
constexpr int OFF_STAT = OFF_X + 1024;
constexpr int OFF_HS = OFF_RING + (127 % kStages) * kChunk;
constexpr int OFF_PART = OFF_HS + 5632;
constexpr int OFF_CTL = OFF_STAT + 256;
constexpr int OFF_BAR = OFF_CTL + 16;
constexpr int SMEM_BYTES = OFF_BAR + 8 * (16 + kStages + 8 + 4);
static_assert(SMEM_BYTES <= 232448 && kLookahead <= kStages, "smem");

constexpr uint32_t kSpinLimit = 1u << 22;

__device__ float2 g_acc[2][4 * kD];
__device__ uint4 g_ll[112 * 4 * 4];
__device__ unsigned g_epoch;
__device__ unsigned g_prog[2];

DEVINL uint32_t smem_u32(const void* p) { return (uint32_t)__cvta_generic_to_shared(p); }
DEVINL void mbar_init(uint32_t bar, uint32_t cnt) {
    asm volatile("mbarrier.init.shared::cta.b64 [%0], %1;" ::"r"(bar), "r"(cnt) : "memory");
}
DEVINL void mbar_expect_tx(uint32_t bar, uint32_t bytes) {
    asm volatile("mbarrier.arrive.expect_tx.shared::cta.b64 _, [%0], %1;" ::"r"(bar), "r"(bytes) : "memory");
}
DEVINL void mbar_arrive(uint32_t bar) {
    asm volatile("mbarrier.arrive.shared::cta.b64 _, [%0];" ::"r"(bar) : "memory");
}
DEVINL void mbar_wait(uint32_t bar, uint32_t parity) {
    uint32_t done, tries = 0;
    do {
        asm volatile(
            "{\n.reg .pred p;\nmbarrier.try_wait.parity.shared::cta.b64 p, [%1], %2;\nselp.u32 %0, 1, 0, p;\n}"
            : "=r"(done) : "r"(bar), "r"(parity) : "memory");
        if (!done && ++tries > kSpinLimit) __trap();
    } while (!done);
}
DEVINL void bulk_load_pol(uint32_t dst, const void* src, uint32_t bytes, uint32_t bar, uint64_t pol) {
    asm volatile("cp.async.bulk.shared::cluster.global.mbarrier::complete_tx::bytes.L2::cache_hint [%0], [%1], %2, [%3], %4;"
                 ::"r"(dst), "l"(src), "r"(bytes), "r"(bar), "l"(pol) : "memory");
}
DEVINL void tma_load_2d(uint32_t dst, const CUtensorMap* map, int c0, int c1, uint32_t bar) {
    asm volatile("cp.async.bulk.tensor.2d.shared::cluster.global.mbarrier::complete_tx::bytes [%0], [%1, {%3, %4}], [%2];"
                 ::"r"(dst), "l"(reinterpret_cast<uint64_t>(map)), "r"(bar), "r"(c0), "r"(c1) : "memory");
}
DEVINL void tmap_prefetch(const CUtensorMap* map) {
    asm volatile("prefetch.tensormap [%0];" ::"l"(reinterpret_cast<uint64_t>(map)) : "memory");
}
DEVINL void ldsm4(uint32_t (&r)[4], uint32_t addr) {
    asm volatile("ldmatrix.sync.aligned.m8n8.x4.shared.b16 {%0,%1,%2,%3}, [%4];"
                 : "=r"(r[0]), "=r"(r[1]), "=r"(r[2]), "=r"(r[3]) : "r"(addr) : "memory");
}
DEVINL void ldsm4t(uint32_t (&r)[4], uint32_t addr) {
    asm volatile("ldmatrix.sync.aligned.m8n8.x4.trans.shared.b16 {%0,%1,%2,%3}, [%4];"
                 : "=r"(r[0]), "=r"(r[1]), "=r"(r[2]), "=r"(r[3]) : "r"(addr) : "memory");
}
DEVINL void mma16816(float (&c)[4], const uint32_t (&a)[4], uint32_t b0, uint32_t b1) {
    asm volatile(
        "mma.sync.aligned.m16n8k16.row.col.f32.bf16.bf16.f32 {%0,%1,%2,%3}, {%4,%5,%6,%7}, {%8,%9}, {%0,%1,%2,%3};"
        : "+f"(c[0]), "+f"(c[1]), "+f"(c[2]), "+f"(c[3])
        : "r"(a[0]), "r"(a[1]), "r"(a[2]), "r"(a[3]), "r"(b0), "r"(b1));
}
DEVINL void bar_cons_() { asm volatile("bar.sync 1, 512;" ::: "memory"); }
#define bar_cons() do { if (live) bar_cons_(); } while (0)
DEVINL float bf16r(float v) { return __bfloat162float(__float2bfloat16_rn(v)); }
DEVINL float bf_lo(uint32_t u) { return __uint_as_float(u << 16); }
DEVINL float bf_hi(uint32_t u) { return __uint_as_float(u & 0xffff0000u); }
DEVINL uint32_t pack_bf16(float lo, float hi) {
    uint32_t r;
    asm("cvt.rn.bf16x2.f32 %0, %1, %2;" : "=r"(r) : "f"(hi), "f"(lo));
    return r;
}
DEVINL float warp_sum(float v) {
#pragma unroll
    for (int o = 16; o > 0; o >>= 1) v += __shfl_xor_sync(0xffffffffu, v, o);
    return v;
}
DEVINL float warp_max(float v) {
#pragma unroll
    for (int o = 16; o > 0; o >>= 1) v = fmaxf(v, __shfl_xor_sync(0xffffffffu, v, o));
    return v;
}
DEVINL float4 ld_relaxed_f4(const void* p) {
    float4 v;
    asm volatile("ld.relaxed.gpu.global.v4.f32 {%0,%1,%2,%3}, [%4];"
                 : "=f"(v.x), "=f"(v.y), "=f"(v.z), "=f"(v.w) : "l"(p) : "memory");
    return v;
}
DEVINL float2 ld_relaxed_f2(const void* p) {
    float2 v;
    asm volatile("ld.relaxed.gpu.global.v2.f32 {%0,%1}, [%2];" : "=f"(v.x), "=f"(v.y) : "l"(p) : "memory");
    return v;
}
DEVINL uint4 ld_relaxed_2x64(const void* p) {
    unsigned long long a, b;
    asm volatile("ld.relaxed.gpu.global.v2.b64 {%0,%1}, [%2];" : "=l"(a), "=l"(b) : "l"(p) : "memory");
    return make_uint4((uint32_t)a, (uint32_t)(a >> 32), (uint32_t)b, (uint32_t)(b >> 32));
}
DEVINL void st_relaxed_64(void* p, uint32_t lo, uint32_t hi) {
    unsigned long long v = (unsigned long long)lo | ((unsigned long long)hi << 32);
    asm volatile("st.relaxed.gpu.global.b64 [%0], %1;" ::"l"(p), "l"(v) : "memory");
}
DEVINL void red_add_f2(void* p, float a, float b) {
    asm volatile("red.relaxed.gpu.global.add.v2.f32 [%0], {%1,%2};" ::"l"(p), "f"(a), "f"(b) : "memory");
}
DEVINL int slot_at(int base, int r) {
    const int s = base % kStages + r;
    return s >= kStages ? s - kStages : s;
}

__global__ void __launch_bounds__(kThreads, 1)
fused_kernel(const __grid_constant__ CUtensorMap tm_wq, const __grid_constant__ CUtensorMap tm_wo,
             const __grid_constant__ CUtensorMap tm_w1, const __grid_constant__ CUtensorMap tm_w3,
             const __grid_constant__ CUtensorMap tm_w2,
             const __nv_bfloat16* __restrict__ x, const __nv_bfloat16* __restrict__ kc,
             const __nv_bfloat16* __restrict__ vc, __nv_bfloat16* __restrict__ out, const uint32_t zero) {
    extern __shared__ __align__(1024) unsigned char smem[];
    const uint32_t sb = smem_u32(smem);
    const int lane = threadIdx.x & 31;
    const bool live = threadIdx.x + zero < 544;
    const int tid = live ? threadIdx.x : lane, warp = tid >> 5;
    const int cta = blockIdx.x;
    const int b = cta >> 5, h = cta & 31;
    const uint32_t bar_full = sb + OFF_BAR, bar_empty = bar_full + 8 * 16, bar_wo = bar_empty + 8 * kStages,
                   bar_ffn = bar_wo + 8 * 8, bar_x = bar_ffn + 8, bar_wfree = bar_x + 8;
    const int role = (cta < kFfn1Ctas) ? 1 : ((cta >= kFfn2First && cta < kFfn2First + kFfn2Ctas) ? 2 : 0);

    const char* kbase = reinterpret_cast<const char*>(kc) + (size_t)cta * (64 * kChunk);
    uint64_t pol;
    asm volatile("createpolicy.fractional.L2::evict_first.b64 %0, 1.0;" : "=l"(pol));
    if (threadIdx.x == 512) {
        tmap_prefetch(&tm_wq);
        mbar_init(bar_full + 8 * 8, 1);
        mbar_init(bar_x, 1);
        asm volatile("fence.mbarrier_init.release.cluster;" ::: "memory");
        asm volatile("fence.proxy.async.shared::cta;" ::: "memory");
        mbar_expect_tx(bar_full + 8 * 8, kChunk);
        bulk_load_pol(sb + OFF_RING, kbase, kChunk, bar_full + 8 * 8, pol);
        mbar_expect_tx(bar_x, 1024);
        asm volatile("cp.async.bulk.shared::cluster.global.mbarrier::complete_tx::bytes [%0], [%1], %2, [%3];"
                     ::"r"(sb + OFF_X), "l"(x + b * kD), "r"(1024), "r"(bar_x) : "memory");
    }
    if (threadIdx.x == 32) {
#pragma unroll
        for (int s = 0; s < 16; s++) if (s != 8) mbar_init(bar_full + 8 * s, 1);
#pragma unroll
        for (int s = 0; s < kStages; s++) mbar_init(bar_empty + 8 * s, 4);
#pragma unroll
        for (int s = 0; s < 9; s++) mbar_init(bar_wo + 8 * s, 1);
        mbar_init(bar_wfree, 16);
        reinterpret_cast<volatile int*>(smem + OFF_CTL)[0] = 0;
        reinterpret_cast<volatile int*>(smem + OFF_CTL)[1] = kLookahead;
        asm volatile("fence.mbarrier_init.release.cluster;" ::: "memory");
        asm volatile("fence.proxy.async.shared::cta;" ::: "memory");
    }
    __syncthreads();
    if (threadIdx.x >= 512) {
        if (lane == 0) {
            const char* vbase = reinterpret_cast<const char*>(vc) + (size_t)cta * (64 * kChunk);
#pragma unroll 1
            for (int k = 0; k < (live ? 8 : 0); k++) {
                mbar_expect_tx(bar_full + 8 * k, kChunk);
                tma_load_2d(sb + OFF_W + k * kChunk, &tm_wq, h * 128, k * 64, bar_full + 8 * k);
            }
            int slot = 1;
            int wslot = 1, waited = 1 - kStages;
            uint32_t wphase = 1;
            const int n_steps = live ? (role ? 132 : 128) : 4;
#pragma unroll 1
            for (int step = live ? 1 : 0; step < n_steps; step++) {
                constexpr unsigned kDryList = 1u | kWoAt << 8 | 128u << 16 | 130u << 24;
                const int c = live ? step : (int)((kDryList >> (8 * step)) & 255);
                if (live) reinterpret_cast<volatile int*>(smem + OFF_CTL)[0] = c;
                int la = reinterpret_cast<volatile int*>(smem + OFF_CTL)[1];
                if (c < kStages || c >= 128) la = kStages;
                while (live && waited <= c - la) {
                    mbar_wait(bar_empty + 8 * wslot, wphase);
                    waited++;
                    if (++wslot == kStages) { wslot = 0; wphase ^= 1; }
                }
                const uint32_t dst = sb + OFF_RING + slot * kChunk;
                if (c < 128) {
                    const char* src = (c < 64) ? kbase + (size_t)c * kChunk : vbase + (size_t)(c - 64) * kChunk;
                    if (live) {
                        mbar_expect_tx(bar_full + 8 * ((c + 8) & 15), kChunk);
                        bulk_load_pol(dst, src, kChunk, bar_full + 8 * ((c + 8) & 15), pol);
                    }
                    if (c == 1) {
                        tmap_prefetch(&tm_wo);
                        if (role == 1) { tmap_prefetch(&tm_w1); tmap_prefetch(&tm_w3); }
                        if (role == 2) tmap_prefetch(&tm_w2);
                    }
                    const int k = (c - kWoAt) / kWoStep;
                    if (c >= kWoAt && k < 8 && c == kWoAt + k * kWoStep) {
                        if (live) {
                            if (k == 0) mbar_wait(bar_wfree, 0);
                            mbar_expect_tx(bar_wo + 8 * k, kChunk);
                            tma_load_2d(sb + OFF_W + k * kChunk, &tm_wo, k * 64, h * 128, bar_wo + 8 * k);
                        }
                    }
                } else {
                    const int k = c - 128;
                    if (k == 0 && live) mbar_wait(bar_full + 8 * ((127 + 8) & 15), ((127 + 8) >> 4) & 1);
                    if (role == 1) {
                        if (k == 0 && live) mbar_expect_tx(bar_ffn, 4 * kChunk);
                        if (live) tma_load_2d(dst, (k & 2) ? &tm_w3 : &tm_w1, cta * 32, (k & 1) * 256, bar_ffn);
                    } else if (role == 2) {
                        if (k == 0 && live) mbar_expect_tx(bar_ffn, 7 * 8192);
                        if (live) tma_load_2d(dst, &tm_w2, (cta - kFfn2First) * 16, k * 512, bar_ffn);
                        if (k < 3 && live) tma_load_2d(dst + 8192, &tm_w2, (cta - kFfn2First) * 16, k * 512 + 256, bar_ffn);
                    }
                }
                if (++slot == kStages) slot = 0;
            }
        }
        if (live) return;
        __syncwarp();
    }

    const int g = lane >> 2, t = lane & 3;
    const int set = warp >> 2;
    const int grp = warp & 3;
    uint32_t mask[8];
    {
        const int dd = (g - 2 * t) & 7;
#pragma unroll
        for (int j = 0; j < 8; j++)
            mask[j] = (j == dd ? 0x0000ffffu : 0u) | (j == ((dd - 1) & 7) ? 0xffff0000u : 0u);
    }
    const uint32_t vrow = sb + OFF_RING + grp * 4096 + ((lane & 7) + (lane >> 4) * 8) * 256 + ((lane >> 3) & 1) * 128;
    const uint32_t krow = sb + OFF_RING + grp * 4096 + ((lane & 7) + ((lane >> 3) & 1) * 8) * 256 + (lane >> 4) * 128;
    unsigned char* const srow = smem + OFF_S + warp * kSPitch;
    const bool diag = (t == (g >> 1));
    const bool godd = (g & 1) != 0;

    const int nit = live ? 16 : 1;
    unsigned epoch = 0;
    if (live) asm volatile("ld.relaxed.gpu.global.u32 %0, [%1];" : "=r"(epoch) : "l"(&g_epoch) : "memory");
    {
        if (live) mbar_wait(bar_x, 0);
        const uint4 xa = reinterpret_cast<const uint4*>(smem + OFF_X)[2 * lane];
        const uint4 xb = reinterpret_cast<const uint4*>(smem + OFF_X)[2 * lane + 1];
        float xv[16];
        xv[0] = bf_lo(xa.x); xv[1] = bf_hi(xa.x); xv[2] = bf_lo(xa.y); xv[3] = bf_hi(xa.y);
        xv[4] = bf_lo(xa.z); xv[5] = bf_hi(xa.z); xv[6] = bf_lo(xa.w); xv[7] = bf_hi(xa.w);
        xv[8] = bf_lo(xb.x); xv[9] = bf_hi(xb.x); xv[10] = bf_lo(xb.y); xv[11] = bf_hi(xb.y);
        xv[12] = bf_lo(xb.z); xv[13] = bf_hi(xb.z); xv[14] = bf_lo(xb.w); xv[15] = bf_hi(xb.w);
        float s = 0.f;
#pragma unroll
        for (int i = 0; i < 16; i++) s += xv[i];
        const float mean = warp_sum(s) * (1.f / kD);
        float v = 0.f;
#pragma unroll
        for (int i = 0; i < 16; i++) { const float d = xv[i] - mean; v += d * d; }
        const float var = warp_sum(v) * (1.f / kD);
        const float den = bf16r(sqrtf(bf16r(bf16r(var) + 1e-5f)));
        const float mb = bf16r(mean);
        uint32_t xn[4];
#pragma unroll
        for (int k = 0; k < 4; k++) {
            const uint32_t u = reinterpret_cast<const uint32_t*>(smem + OFF_X)[(set + 4 * (k >> 1)) * 32 + grp * 8 + t + (k & 1) * 4];
            xn[k] = pack_bf16(bf16r(bf_lo(u) - mb) / den, bf16r(bf_hi(u) - mb) / den);
        }
        float c0[4] = {0.f, 0.f, 0.f, 0.f}, c1[4] = {0.f, 0.f, 0.f, 0.f};
#pragma unroll 1
        for (int k = 0; k < 2; k++) {
            const int sl = 4 * k + set;
            const uint32_t pp0 = k ? xn[2] : xn[0], pp1 = k ? xn[3] : xn[1];
            if (live) mbar_wait(bar_full + 8 * sl, 0);
#pragma unroll
            for (int j = 0; j < 8; j += 2) {
                uint32_t a0[4], a1[4];
                ldsm4t(a0, vrow + OFF_W + sl * kChunk + ((lane + j) & 7) * 16);
                ldsm4t(a1, vrow + OFF_W + sl * kChunk + ((lane + j + 1) & 7) * 16);
                mma16816(c0, a0, pp0 & mask[j], pp1 & mask[j]);
                mma16816(c1, a1, pp0 & mask[j + 1], pp1 & mask[j + 1]);
            }
        }
        if (lane == 0 && live) mbar_arrive(bar_wfree + ((__float_as_uint(c0[0]) ^ __float_as_uint(c1[0])) & zero));
        float* qp = reinterpret_cast<float*>(srow);
        if (live) {
            qp[(2 * t) * 8 + g] = c0[0] + c1[0];
            qp[(2 * t + 1) * 8 + g] = c0[1] + c1[1];
            qp[(2 * t + 8) * 8 + g] = c0[2] + c1[2];
            qp[(2 * t + 9) * 8 + g] = c0[3] + c1[3];
        }
        bar_cons();
        if (tid < 128) {
            const float* qs = reinterpret_cast<const float*>(smem + OFF_S) + tid;
            float q = 0.f;
#pragma unroll
            for (int w = 0; w < 16; w++) q += qs[w * (kSPitch / 4)];
            if (live) reinterpret_cast<__nv_bfloat16*>(smem + OFF_Q)[tid] = __float2bfloat16_rn(q);
        }
        bar_cons();
    }
    int sl = set;
    {
        uint32_t bq0[8], bq1[8];
        const uint32_t* q2 = reinterpret_cast<const uint32_t*>(smem + OFF_Q);
#pragma unroll
        for (int j = 0; j < 8; j++) {
            bq0[j] = q2[((g + j) & 7) * 4 + t];
            bq1[j] = q2[32 + ((g + j) & 7) * 4 + t];
        }
        float* sc = reinterpret_cast<float*>(srow);
        float mx = -INFINITY;
#pragma unroll 1
        for (int it = 0; it < nit; it++) {
            const int n = it + 2;
            if (live) mbar_wait(bar_full + 8 * ((n & 3) * 4 + set), (n >> 2) & 1);
            float c0[4] = {0.f, 0.f, 0.f, 0.f}, c1[4] = {0.f, 0.f, 0.f, 0.f};
#pragma unroll
            for (int j = 0; j < 8; j += 2) {
                uint32_t a0[4], a1[4];
                ldsm4(a0, krow + sl * kChunk + ((lane + j) & 7) * 16);
                ldsm4(a1, krow + sl * kChunk + ((lane + j + 1) & 7) * 16);
                mma16816(c0, a0, bq0[j], bq1[j]);
                mma16816(c1, a1, bq0[j + 1], bq1[j + 1]);
            }
            if (lane == 0 && live) mbar_arrive(bar_empty + 8 * sl + ((__float_as_uint(c0[0]) ^ __float_as_uint(c1[0])) & zero));
            const float slo = bf16r(bf16r(godd ? c0[1] + c1[1] : c0[0] + c1[0]) * 0.08838834764831845f);
            const float shi = bf16r(bf16r(godd ? c0[3] + c1[3] : c0[2] + c1[2]) * 0.08838834764831845f);
            if (diag && live) {
                sc[it * 16 + g] = slo;
                sc[it * 16 + g + 8] = shi;
                mx = fmaxf(mx, fmaxf(slo, shi));
            }
            sl += 4;
            if (sl >= kStages) sl -= kStages;
        }
        float* smax = reinterpret_cast<float*>(smem + OFF_STAT);
        float* ssum = smax + 16;
        mx = warp_max(mx);
        if (lane == 0 && live) smax[warp] = mx;
        bar_cons();
        {
            const float4* p4 = reinterpret_cast<const float4*>(smax);
            const float4 m0 = p4[0], m1 = p4[1], m2 = p4[2], m3 = p4[3];
            mx = fmaxf(fmaxf(fmaxf(m0.x, m0.y), fmaxf(m0.z, m0.w)), fmaxf(fmaxf(m1.x, m1.y), fmaxf(m1.z, m1.w)));
            mx = fmaxf(mx, fmaxf(fmaxf(fmaxf(m2.x, m2.y), fmaxf(m2.z, m2.w)), fmaxf(fmaxf(m3.x, m3.y), fmaxf(m3.z, m3.w))));
        }
        const float cs = 1.4426950408889634f;
        const float4 s0 = reinterpret_cast<const float4*>(sc)[2 * lane], s1 = reinterpret_cast<const float4*>(sc)[2 * lane + 1];
        float e[8] = {s0.x, s0.y, s0.z, s0.w, s1.x, s1.y, s1.z, s1.w};
        float sum = 0.f;
#pragma unroll
        for (int i = 0; i < 8; i++) { e[i] = exp2f((e[i] - mx) * cs); sum += e[i]; }
        sum = warp_sum(sum);
        if (lane == 0 && live) ssum[warp] = sum;
        bar_cons();
        {
            const float4* p4 = reinterpret_cast<const float4*>(ssum);
            const float4 m0 = p4[0], m1 = p4[1], m2 = p4[2], m3 = p4[3];
            sum = ((m0.x + m0.y) + (m0.z + m0.w)) + ((m1.x + m1.y) + (m1.z + m1.w)) +
                  ((m2.x + m2.y) + (m2.z + m2.w)) + ((m3.x + m3.y) + (m3.z + m3.w));
        }
        const float inv = 1.f / sum;
        if (live) reinterpret_cast<uint4*>(srow + 512)[lane] =
            make_uint4(pack_bf16(e[0] * inv, e[1] * inv), pack_bf16(e[2] * inv, e[3] * inv),
                       pack_bf16(e[4] * inv, e[5] * inv), pack_bf16(e[6] * inv, e[7] * inv));
        __syncwarp();
    }
    const int par = epoch & 1;
    const unsigned tag = epoch + 1;
    if (live) {
        if (tid < 16) g_acc[par ^ 1][cta * 16 + tid] = make_float2(0.f, 0.f);
    }
    float oc[4];
    uint32_t wf[8][2][4];
    const int r8 = lane & 7;
    const uint32_t wbase = sb + OFF_W + (warp >> 1) * kChunk + (r8 + (lane >> 4) * 8) * 128;
    const int cu = (warp & 1) * 4 + ((lane >> 3) & 1);
    {
        const uint32_t* pw = reinterpret_cast<const uint32_t*>(srow + 512) + t;
        float c0[4] = {0.f, 0.f, 0.f, 0.f}, c1[4] = {0.f, 0.f, 0.f, 0.f};
#pragma unroll 1
        for (int it = 0; it < nit; it++) {
            const int n = it + 18;
            const uint32_t pp0 = pw[it * 8], pp1 = pw[it * 8 + 4];
            if (it == nit - 1) {
                if (live) mbar_wait(bar_wo + 8 * (warp >> 1), 0);
#pragma unroll
                for (int s = 0; s < kWfPre; s++) {
                    ldsm4t(wf[s][0], wbase + s * 2048 + ((cu ^ r8) * 16));
                    ldsm4t(wf[s][1], wbase + s * 2048 + (((cu + 2) ^ r8) * 16));
                }
            }
            if (live) mbar_wait(bar_full + 8 * ((n & 3) * 4 + set), (n >> 2) & 1);
#pragma unroll
            for (int j = 0; j < 8; j += 2) {
                uint32_t a0[4], a1[4];
                ldsm4t(a0, vrow + sl * kChunk + ((lane + j) & 7) * 16);
                ldsm4t(a1, vrow + sl * kChunk + ((lane + j + 1) & 7) * 16);
                mma16816(c0, a0, pp0 & mask[j], pp1 & mask[j]);
                mma16816(c1, a1, pp0 & mask[j + 1], pp1 & mask[j + 1]);
            }
            if (lane == 0 && live) mbar_arrive(bar_empty + 8 * sl + ((__float_as_uint(c0[0]) ^ __float_as_uint(c1[0])) & zero));
            sl += 4;
            if (sl >= kStages) sl -= kStages;
        }
#pragma unroll
        for (int k = 0; k < 4; k++) oc[k] = c0[k] + c1[k];
    }
    {
        if (warp >= 8) {
            if (live) {
                reinterpret_cast<float4*>(srow)[lane] = make_float4(oc[0], oc[1], oc[2], oc[3]);
                asm volatile("bar.arrive %0, 64;" ::"r"(2 + (warp & 7)) : "memory");
            }
        }
#pragma unroll
        for (int s = kWfPre; s < 8; s++) {
            ldsm4t(wf[s][0], wbase + s * 2048 + ((cu ^ r8) * 16));
            ldsm4t(wf[s][1], wbase + s * 2048 + (((cu + 2) ^ r8) * 16));
        }
        if (warp < 8) {
            if (live) asm volatile("bar.sync %0, 64;" ::"r"(2 + warp) : "memory");
            const float4 o2 = reinterpret_cast<const float4*>(srow + 8 * kSPitch)[lane];
            __nv_bfloat16* op = reinterpret_cast<__nv_bfloat16*>(srow);
            if (live) {
                op[(2 * t) * 8 + g] = __float2bfloat16_rn(oc[0] + o2.x);
                op[(2 * t + 1) * 8 + g] = __float2bfloat16_rn(oc[1] + o2.y);
                op[(2 * t + 8) * 8 + g] = __float2bfloat16_rn(oc[2] + o2.z);
                op[(2 * t + 9) * 8 + g] = __float2bfloat16_rn(oc[3] + o2.w);
            }
        }
        bar_cons();
        float acc[4][4];
#pragma unroll
        for (int a = 0; a < 4; a++)
#pragma unroll
            for (int k = 0; k < 4; k++) acc[a][k] = 0.f;
        const uint32_t brow = sb + OFF_S + (lane & 7) * kSPitch + (lane >> 3) * 16;
#pragma unroll
        for (int s2 = 0; s2 < 4; s2++) {
            uint32_t bA[4];
            ldsm4(bA, brow + s2 * 64);
            mma16816(acc[0], wf[s2 * 2][0], bA[0], bA[1]);
            mma16816(acc[2], wf[s2 * 2][1], bA[0], bA[1]);
            mma16816(acc[1], wf[s2 * 2 + 1][0], bA[2], bA[3]);
            mma16816(acc[3], wf[s2 * 2 + 1][1], bA[2], bA[3]);
        }
        const float v0 = (acc[0][0] + acc[0][1]) + (acc[1][0] + acc[1][1]);
        const float v1 = (acc[0][2] + acc[0][3]) + (acc[1][2] + acc[1][3]);
        const float v2 = (acc[2][0] + acc[2][1]) + (acc[3][0] + acc[3][1]);
        const float v3 = (acc[2][2] + acc[2][3]) + (acc[3][2] + acc[3][3]);
        const bool o1 = (t & 1) != 0, o2 = (t & 2) != 0;
        const float ra = (o1 ? v1 : v0) + __shfl_xor_sync(0xffffffffu, o1 ? v0 : v1, 1);
        const float rb = (o1 ? v3 : v2) + __shfl_xor_sync(0xffffffffu, o1 ? v2 : v3, 1);
        const float r = (o2 ? rb : ra) + __shfl_xor_sync(0xffffffffu, o2 ? ra : rb, 2);
        if (live) {
            red_add_f2(&g_acc[par][b * kD + warp * 32 + (t >> 1) * 16 + (t & 1) * 8 + g], r, 1.0f);
        }
    }
    if (role == 0) {
        if (!live) goto monitor;
        return;
    }
    {

    uint32_t af[8][4];
    const int rr = (lane & 7) + (lane >> 4) * 8, cc = (lane >> 3) & 1;
    constexpr uint32_t off_hs = OFF_HS, off_part = OFF_PART;
    float* part = reinterpret_cast<float*>(smem + off_part);

    if (role == 1) {
        const int bb = tid >> 7, c4 = (tid & 127) * 4;
        uint2 xr = make_uint2(0u, 0u);
        if (live) asm volatile("ld.global.nc.v2.u32 {%0,%1}, [%2];" : "=r"(xr.x), "=r"(xr.y) : "l"(x + bb * kD + c4));
        if (tid < 64 && live) reinterpret_cast<uint4*>(smem + off_hs + 4 * 1040)[tid] = make_uint4(0x3f803f80u, 0x3f803f80u, 0x3f803f80u, 0x3f803f80u);
        const float4* src = reinterpret_cast<const float4*>(&g_acc[par][bb * kD + c4]);
        float4 u0 = make_float4(0.f, 0.f, 0.f, 0.f), u1 = u0;
        uint32_t tries = 0;
        {
            while (live && lane == 0) {
                const float2 u = ld_relaxed_f2(src);
                if (u.y == 32.f) break;
                if (++tries > kSpinLimit) __trap();
            }
            __syncwarp();
        }
        while (live) {
            u0 = ld_relaxed_f4(src);
            u1 = ld_relaxed_f4(src + 1);
            if (u0.y == 32.f && u0.w == 32.f && u1.y == 32.f && u1.w == 32.f) break;
            if (++tries > kSpinLimit) __trap();
        }
        const uint32_t x0 = xr.x, x1 = xr.y;
        const float h0 = bf16r(bf_lo(x0) + bf16r(u0.x)), h1 = bf16r(bf_hi(x0) + bf16r(u0.z));
        const float h2 = bf16r(bf_lo(x1) + bf16r(u1.x)), h3 = bf16r(bf_hi(x1) + bf16r(u1.z));
        if (live) *reinterpret_cast<uint2*>(smem + off_hs + bb * 1040 + c4 * 2) = make_uint2(pack_bf16(h0, h1), pack_bf16(h2, h3));
        const int kq = warp >> 2;
        if (live) mbar_wait(bar_ffn, 0);
        {
            const uint32_t box = sb + OFF_RING + slot_at(128, (warp & 2) + (kq >> 1)) * kChunk;
#pragma unroll
            for (int s = 0; s < 8; s++) {
                const int r = (kq & 1) * 128 + s * 16 + rr;
                ldsm4t(af[s], box + r * 64 + ((((warp & 1) * 2 + cc) ^ ((r >> 1) & 3)) * 16));
            }
        }
        bar_cons();
        float c0[4] = {0.f, 0.f, 0.f, 0.f}, c1[4] = {0.f, 0.f, 0.f, 0.f};
        float q0[4] = {0.f, 0.f, 0.f, 0.f}, q1[4] = {0.f, 0.f, 0.f, 0.f};
        const uint32_t brow = sb + off_hs + min(lane & 7, 4) * 1040 + (kq * 128 + (lane >> 3) * 8) * 2;
        const bool statw = (warp & 3) == kq;
#pragma unroll
        for (int s2 = 0; s2 < 4; s2++) {
            uint32_t bf[4];
            ldsm4(bf, brow + s2 * 64);
            mma16816(c0, af[2 * s2], bf[0], bf[1]);
            mma16816(c1, af[2 * s2 + 1], bf[2], bf[3]);
            if (statw) {
                const uint32_t a0[4] = {bf[0], 0u, bf[1], 0u}, a1[4] = {bf[2], 0u, bf[3], 0u};
                mma16816(q0, a0, bf[0], bf[1]);
                mma16816(q1, a1, bf[2], bf[3]);
            }
        }
        if (t < 3 && live) {
            float* pw = part + ((warp & 3) * 16 + g) * 28 + t * 8 + kq;
            pw[0] = c0[0] + c1[0]; pw[4] = c0[1] + c1[1];
            pw[224] = c0[2] + c1[2]; pw[228] = c0[3] + c1[3];
            if (statw) { float* ps = part + (64 + g) * 28 + t * 8 + kq; ps[0] = q0[0] + q1[0]; ps[4] = q0[1] + q1[1]; }
        }
        bar_cons();
        if (tid < 128) {
            const int eb = tid & 3, fl = tid >> 2, tile = fl >> 4, m = fl & 15;
            const float4* p4 = reinterpret_cast<const float4*>(part);
            const float4 vg = p4[(tile * 16 + m) * 7 + eb], vgs = p4[(tile * 16 + m) * 7 + 4];
            const float4 vu = p4[((tile + 2) * 16 + m) * 7 + eb], vus = p4[((tile + 2) * 16 + m) * 7 + 4];
            const float4 vq = p4[(64 + eb) * 7 + eb], vs = p4[(64 + 4) * 7 + eb];
            const float gr = (vg.x + vg.y) + (vg.z + vg.w), gs = (vgs.x + vgs.y) + (vgs.z + vgs.w);
            const float ur = (vu.x + vu.y) + (vu.z + vu.w), us = (vus.x + vus.y) + (vus.z + vus.w);
            const float mean = ((vs.x + vs.y) + (vs.z + vs.w)) * (1.f / kD);
            const float var = fmaxf(((vq.x + vq.y) + (vq.z + vq.w)) * (1.f / kD) - mean * mean, 0.f);
            float sq, rden;
            asm("sqrt.approx.f32 %0, %1;" : "=f"(sq) : "f"(bf16r(bf16r(var) + 1e-5f)));
            asm("rcp.approx.f32 %0, %1;" : "=f"(rden) : "f"(bf16r(sq)));
            const float mb = bf16r(mean);
            const float gate = bf16r((gr - mb * gs) * rden);
            const float up = bf16r((ur - mb * us) * rden);
            const float act = bf16r(__fdividef(gate, 1.f + __expf(-gate)));
            const float hh = bf16r(act * up);
            const float hn = __shfl_xor_sync(0xffffffffu, hh, 4);
            if ((fl & 1) == 0 && live) {
                const int ks = cta * 2 + tile;
                const uint32_t pk = pack_bf16(hh, hn);
                st_relaxed_64(reinterpret_cast<char*>(&g_ll[(ks * 4 + eb) * 4 + ((m & 7) >> 1)]) + (m >> 3) * 8, pk, tag);
            }
        }
    } else {
        const int c0col = (cta - kFfn2First) * 16;
        float hres = 0.f;
        const int oo = tid >> 2, om = oo >> 2, ob = oo & 3;
        {
            uint32_t tries = 0;
            while (live) {
                bool ok = true;
                if (lane < 4) ok = ld_relaxed_f2(&g_acc[par][lane * kD + c0col + (warp & 15)]).y == 32.f;
                if (__all_sync(0xffffffffu, ok)) break;
                if (++tries > kSpinLimit) __trap();
            }
        }
        if (tid < 256 && (tid & 3) == 0 && live) {
            const float xv = __bfloat162float(x[ob * kD + c0col + om]);
            float2 u;
            uint32_t tries = 0;
            while (true) {
                u = ld_relaxed_f2(&g_acc[par][ob * kD + c0col + om]);
                if (u.y == 32.f) break;
                if (++tries > kSpinLimit) __trap();
            }
            hres = bf16r(xv + bf16r(u.x));
        }
        if (live) mbar_wait(bar_ffn, 0);
#pragma unroll
        for (int s = 0; s < 7; s++) {
            const int f = warp * 112 + s * 16 + rr;
            const uint32_t box = sb + OFF_RING + slot_at(128, f >> 9) * kChunk;
            ldsm4t(af[s], box + (f & 511) * 32 + ((cc ^ ((f >> 2) & 1)) * 16));
        }
        uint4 ll[7];
#pragma unroll
        for (int s = 0; s < 7; s++) ll[s] = make_uint4(0u, 0u, 0u, 0u);
        const uint4* lsrc = &g_ll[(warp * 7 * 4 + (g & 3)) * 4 + t];
        uint32_t tries = 0;
        while (live) {
            bool ok = true;
#pragma unroll
            for (int s = 0; s < 7; s++) ll[s] = ld_relaxed_2x64(lsrc + s * 16);
#pragma unroll
            for (int s = 0; s < 7; s++) ok = ok && (ll[s].y == tag) && (ll[s].w == tag);
            if (__all_sync(0xffffffffu, ok)) break;
            if (++tries > kSpinLimit) __trap();
        }
        float c0[4] = {0.f, 0.f, 0.f, 0.f}, c1[4] = {0.f, 0.f, 0.f, 0.f};
#pragma unroll
        for (int s = 0; s < 7; s++) {
            if (s & 1) mma16816(c1, af[s], ll[s].x, ll[s].z);
            else mma16816(c0, af[s], ll[s].x, ll[s].z);
        }
        if (t < 2 && live) {
            float* pw = part + (g * 4 + 2 * t) * 16 + warp;
            pw[0] = c0[0] + c1[0]; pw[16] = c0[1] + c1[1];
            pw[512] = c0[2] + c1[2]; pw[528] = c0[3] + c1[3];
        }
        bar_cons();
        if (tid < 256) {
            const int qq = tid & 3;
            const float4 pv = reinterpret_cast<const float4*>(part)[tid];
            float s = (pv.x + pv.y) + (pv.z + pv.w);
            s += __shfl_xor_sync(0xffffffffu, s, 1);
            s += __shfl_xor_sync(0xffffffffu, s, 2);
            if (qq == 0 && live) out[ob * kD + c0col + om] = __float2bfloat16_rn(hres + bf16r(s));
        }
        if (cta == kFfn2First && tid == 0 && live) g_epoch = epoch + 1;
    }
    }
monitor:
    if (threadIdx.x == 544) {
        unsigned ep;
        asm volatile("ld.relaxed.gpu.global.u32 %0, [%1];" : "=r"(ep) : "l"(&g_epoch) : "memory");
        unsigned* pp = &g_prog[ep & 1];
        if (cta == 0) g_prog[(ep & 1) ^ 1] = 0;
        int last = 0;
        for (uint32_t tries = 0; tries < kSpinLimit; tries++) {
            const int my = reinterpret_cast<volatile int*>(smem + OFF_CTL)[0];
            unsigned tot;
            asm volatile("atom.relaxed.gpu.global.add.u32 %0, [%1], %2;" : "=r"(tot) : "l"(pp), "r"(my - last) : "memory");
            tot += my - last;
            last = my;
            if (my >= 127) break;
            const int diff = my * 128 - (int)tot;
            reinterpret_cast<volatile int*>(smem + OFF_CTL)[1] = diff < 0 ? kStages : kLookahead;
            __nanosleep(300);
        }
    }
}

typedef CUresult (*EncodeFn)(CUtensorMap*, CUtensorMapDataType, cuuint32_t, void*, const cuuint64_t*, const cuuint64_t*,
                             const cuuint32_t*, const cuuint32_t*, CUtensorMapInterleave, CUtensorMapSwizzle,
                             CUtensorMapL2promotion, CUtensorMapFloatOOBfill);

static void make_map(EncodeFn enc, CUtensorMap* m, void* ptr, uint64_t cols, uint64_t rows, uint32_t bc, uint32_t br,
                     CUtensorMapSwizzle sw) {
    cuuint64_t dims[2] = {cols, rows};
    cuuint64_t strides[1] = {cols * 2};
    cuuint32_t box[2] = {bc, br};
    cuuint32_t es[2] = {1, 1};
    enc(m, CU_TENSOR_MAP_DATA_TYPE_BFLOAT16, 2, ptr, dims, strides, box, es, CU_TENSOR_MAP_INTERLEAVE_NONE, sw,
        CU_TENSOR_MAP_L2_PROMOTION_L2_128B, CU_TENSOR_MAP_FLOAT_OOB_FILL_NONE);
}

}

extern "C" void kernel_launch(void* const* d_in, const int* in_sizes, int n_in, void* d_out, int out_size) {
    (void)in_sizes; (void)n_in; (void)out_size;
    using namespace fused;
    static EncodeFn enc = nullptr;
    if (!enc) {
        void* fn = nullptr;
        cudaDriverEntryPointQueryResult st;
        cudaGetDriverEntryPoint("cuTensorMapEncodeTiled", &fn, cudaEnableDefault, &st);
        enc = (EncodeFn)fn;
        cudaFuncSetAttribute(fused_kernel, cudaFuncAttributeMaxDynamicSharedMemorySize, SMEM_BYTES);
    }
    CUtensorMap mq, mo, m1, m3, m2;
    make_map(enc, &mq, d_in[3], kHD, kD, 128, 64, CU_TENSOR_MAP_SWIZZLE_NONE);
    make_map(enc, &mo, d_in[4], kD, kHD, 64, 128, CU_TENSOR_MAP_SWIZZLE_128B);
    make_map(enc, &m1, d_in[6], kF, kD, 32, 256, CU_TENSOR_MAP_SWIZZLE_64B);
    make_map(enc, &m3, d_in[7], kF, kD, 32, 256, CU_TENSOR_MAP_SWIZZLE_64B);
    make_map(enc, &m2, d_in[8], kD, kF, 16, 256, CU_TENSOR_MAP_SWIZZLE_32B);
    fused_kernel<<<kCtas, kThreads, SMEM_BYTES>>>(
        mq, mo, m1, m3, m2, (const __nv_bfloat16*)d_in[0], (const __nv_bfloat16*)d_in[1], (const __nv_bfloat16*)d_in[2],
        (__nv_bfloat16*)d_out, 0u);
}
```

```cpp
#include <cuda_runtime.h>
#include <cuda.h>
#include <cuda_bf16.h>
#include <stdint.h>

#define DEVINL __device__ __forceinline__

namespace fused {

constexpr int kD = 512, kF = 1792, kHD = 4096;
constexpr int kCtas = 128;
constexpr int kThreads = 576;
constexpr int kChunk = 16384;
constexpr int kStages = 5;
constexpr int kLookahead = 4;
constexpr int kWoAt = 16, kWoStep = 4;
constexpr int kWfPre = 6;
constexpr int kFfn1Ctas = 56;
constexpr int kFfn2First = 64;
constexpr int kFfn2Ctas = 32;

constexpr int OFF_RING = 0;
constexpr int OFF_W = kStages * kChunk;
constexpr int kSPitch = 1040;
constexpr int OFF_S = OFF_W + 8 * kChunk;
constexpr int OFF_Q = OFF_S + 16 * kSPitch;
constexpr int OFF_X = OFF_Q + 256;
constexpr int OFF_STAT = OFF_X + 1024;
constexpr int OFF_HS = OFF_RING + (127 % kStages) * kChunk;
constexpr int OFF_PART = OFF_HS + 5632;
constexpr int OFF_CTL = OFF_STAT + 256;
constexpr int OFF_BAR = OFF_CTL + 16;
constexpr int SMEM_BYTES = OFF_BAR + 8 * (16 + kStages + 8 + 4);
static_assert(SMEM_BYTES <= 232448 && kLookahead <= kStages, "smem");

constexpr uint32_t kSpinLimit = 1u << 22;

__device__ float2 g_acc[2][4 * kD];
__device__ uint4 g_ll[112 * 4 * 4];
__device__ unsigned g_epoch;
__device__ unsigned g_prog[2];

DEVINL uint32_t smem_u32(const void* p) { return (uint32_t)__cvta_generic_to_shared(p); }
DEVINL void mbar_init(uint32_t bar, uint32_t cnt) {
    asm volatile("mbarrier.init.shared::cta.b64 [%0], %1;" ::"r"(bar), "r"(cnt) : "memory");
}
DEVINL void mbar_expect_tx(uint32_t bar, uint32_t bytes) {
    asm volatile("mbarrier.arrive.expect_tx.shared::cta.b64 _, [%0], %1;" ::"r"(bar), "r"(bytes) : "memory");
}
DEVINL void mbar_arrive(uint32_t bar) {
    asm volatile("mbarrier.arrive.shared::cta.b64 _, [%0];" ::"r"(bar) : "memory");
}
DEVINL void mbar_wait(uint32_t bar, uint32_t parity) {
    uint32_t done, tries = 0;
    do {
        asm volatile(
            "{\n.reg .pred p;\nmbarrier.try_wait.parity.shared::cta.b64 p, [%1], %2;\nselp.u32 %0, 1, 0, p;\n}"
            : "=r"(done) : "r"(bar), "r"(parity) : "memory");
        if (!done && ++tries > kSpinLimit) __trap();
    } while (!done);
}
DEVINL void bulk_load_pol(uint32_t dst, const void* src, uint32_t bytes, uint32_t bar, uint64_t pol) {
    asm volatile("cp.async.bulk.shared::cluster.global.mbarrier::complete_tx::bytes.L2::cache_hint [%0], [%1], %2, [%3], %4;"
                 ::"r"(dst), "l"(src), "r"(bytes), "r"(bar), "l"(pol) : "memory");
}
DEVINL void tma_load_2d(uint32_t dst, const CUtensorMap* map, int c0, int c1, uint32_t bar) {
    asm volatile("cp.async.bulk.tensor.2d.shared::cluster.global.mbarrier::complete_tx::bytes [%0], [%1, {%3, %4}], [%2];"
                 ::"r"(dst), "l"(reinterpret_cast<uint64_t>(map)), "r"(bar), "r"(c0), "r"(c1) : "memory");
}
DEVINL void tmap_prefetch(const CUtensorMap* map) {
    asm volatile("prefetch.tensormap [%0];" ::"l"(reinterpret_cast<uint64_t>(map)) : "memory");
}
DEVINL void ldsm4(uint32_t (&r)[4], uint32_t addr) {
    asm volatile("ldmatrix.sync.aligned.m8n8.x4.shared.b16 {%0,%1,%2,%3}, [%4];"
                 : "=r"(r[0]), "=r"(r[1]), "=r"(r[2]), "=r"(r[3]) : "r"(addr) : "memory");
}
DEVINL void ldsm4t(uint32_t (&r)[4], uint32_t addr) {
    asm volatile("ldmatrix.sync.aligned.m8n8.x4.trans.shared.b16 {%0,%1,%2,%3}, [%4];"
                 : "=r"(r[0]), "=r"(r[1]), "=r"(r[2]), "=r"(r[3]) : "r"(addr) : "memory");
}
DEVINL void mma16816(float (&c)[4], const uint32_t (&a)[4], uint32_t b0, uint32_t b1) {
    asm volatile(
        "mma.sync.aligned.m16n8k16.row.col.f32.bf16.bf16.f32 {%0,%1,%2,%3}, {%4,%5,%6,%7}, {%8,%9}, {%0,%1,%2,%3};"
        : "+f"(c[0]), "+f"(c[1]), "+f"(c[2]), "+f"(c[3])
        : "r"(a[0]), "r"(a[1]), "r"(a[2]), "r"(a[3]), "r"(b0), "r"(b1));
}
DEVINL void bar_cons_() { asm volatile("bar.sync 1, 512;" ::: "memory"); }
#define bar_cons() do { if (live) bar_cons_(); } while (0)
DEVINL float bf16r(float v) { return __bfloat162float(__float2bfloat16_rn(v)); }
DEVINL float bf_lo(uint32_t u) { return __uint_as_float(u << 16); }
DEVINL float bf_hi(uint32_t u) { return __uint_as_float(u & 0xffff0000u); }
DEVINL uint32_t pack_bf16(float lo, float hi) {
    uint32_t r;
    asm("cvt.rn.bf16x2.f32 %0, %1, %2;" : "=r"(r) : "f"(hi), "f"(lo));
    return r;
}
DEVINL float warp_sum(float v) {
#pragma unroll
    for (int o = 16; o > 0; o >>= 1) v += __shfl_xor_sync(0xffffffffu, v, o);
    return v;
}
DEVINL float warp_max(float v) {
#pragma unroll
    for (int o = 16; o > 0; o >>= 1) v = fmaxf(v, __shfl_xor_sync(0xffffffffu, v, o));
    return v;
}
DEVINL float4 ld_relaxed_f4(const void* p) {
    float4 v;
    asm volatile("ld.relaxed.gpu.global.v4.f32 {%0,%1,%2,%3}, [%4];"
                 : "=f"(v.x), "=f"(v.y), "=f"(v.z), "=f"(v.w) : "l"(p) : "memory");
    return v;
}
DEVINL float2 ld_relaxed_f2(const void* p) {
    float2 v;
    asm volatile("ld.relaxed.gpu.global.v2.f32 {%0,%1}, [%2];" : "=f"(v.x), "=f"(v.y) : "l"(p) : "memory");
    return v;
}
DEVINL uint4 ld_relaxed_2x64(const void* p) {
    unsigned long long a, b;
    asm volatile("ld.relaxed.gpu.global.v2.b64 {%0,%1}, [%2];" : "=l"(a), "=l"(b) : "l"(p) : "memory");
    return make_uint4((uint32_t)a, (uint32_t)(a >> 32), (uint32_t)b, (uint32_t)(b >> 32));
}
DEVINL void st_relaxed_64(void* p, uint32_t lo, uint32_t hi) {
    unsigned long long v = (unsigned long long)lo | ((unsigned long long)hi << 32);
    asm volatile("st.relaxed.gpu.global.b64 [%0], %1;" ::"l"(p), "l"(v) : "memory");
}
DEVINL void red_add_f2(void* p, float a, float b) {
    asm volatile("red.relaxed.gpu.global.add.v2.f32 [%0], {%1,%2};" ::"l"(p), "f"(a), "f"(b) : "memory");
}
DEVINL int slot_at(int base, int r) {
    const int s = base % kStages + r;
    return s >= kStages ? s - kStages : s;
}

__global__ void __launch_bounds__(kThreads, 1)
fused_kernel(const __grid_constant__ CUtensorMap tm_wq, const __grid_constant__ CUtensorMap tm_wo,
             const __grid_constant__ CUtensorMap tm_w1, const __grid_constant__ CUtensorMap tm_w3,
             const __grid_constant__ CUtensorMap tm_w2,
             const __nv_bfloat16* __restrict__ x, const __nv_bfloat16* __restrict__ kc,
             const __nv_bfloat16* __restrict__ vc, __nv_bfloat16* __restrict__ out, const uint32_t zero) {
    extern __shared__ __align__(1024) unsigned char smem[];
    const uint32_t sb = smem_u32(smem);
    const int lane = threadIdx.x & 31;
    const bool live = threadIdx.x + zero < 544;
    const int tid = live ? threadIdx.x : lane, warp = tid >> 5;
    const int cta = blockIdx.x;
    const int b = cta >> 5, h = cta & 31;
    const uint32_t bar_full = sb + OFF_BAR, bar_empty = bar_full + 8 * 16, bar_wo = bar_empty + 8 * kStages,
                   bar_ffn = bar_wo + 8 * 8, bar_x = bar_ffn + 8, bar_wfree = bar_x + 8;
    const int role = (cta < kFfn1Ctas) ? 1 : ((cta >= kFfn2First && cta < kFfn2First + kFfn2Ctas) ? 2 : 0);

    const char* kbase = reinterpret_cast<const char*>(kc) + (size_t)cta * (64 * kChunk);
    uint64_t pol;
    asm volatile("createpolicy.fractional.L2::evict_first.b64 %0, 1.0;" : "=l"(pol));
    if (threadIdx.x == 512) {
        tmap_prefetch(&tm_wq);
        mbar_init(bar_full + 8 * 8, 1);
        mbar_init(bar_x, 1);
        asm volatile("fence.mbarrier_init.release.cluster;" ::: "memory");
        asm volatile("fence.proxy.async.shared::cta;" ::: "memory");
        mbar_expect_tx(bar_full + 8 * 8, kChunk);
        bulk_load_pol(sb + OFF_RING, kbase, kChunk, bar_full + 8 * 8, pol);
        mbar_expect_tx(bar_x, 1024);
        asm volatile("cp.async.bulk.shared::cluster.global.mbarrier::complete_tx::bytes [%0], [%1], %2, [%3];"
                     ::"r"(sb + OFF_X), "l"(x + b * kD), "r"(1024), "r"(bar_x) : "memory");
    }
    if (threadIdx.x == 32) {
#pragma unroll
        for (int s = 0; s < 16; s++) if (s != 8) mbar_init(bar_full + 8 * s, 1);
#pragma unroll
        for (int s = 0; s < kStages; s++) mbar_init(bar_empty + 8 * s, 4);
#pragma unroll
        for (int s = 0; s < 9; s++) mbar_init(bar_wo + 8 * s, 1);
        mbar_init(bar_wfree, 16);
        reinterpret_cast<volatile int*>(smem + OFF_CTL)[0] = 0;
        reinterpret_cast<volatile int*>(smem + OFF_CTL)[1] = kLookahead;
        asm volatile("fence.mbarrier_init.release.cluster;" ::: "memory");
        asm volatile("fence.proxy.async.shared::cta;" ::: "memory");
    }
    __syncthreads();
    if (threadIdx.x >= 512) {
        if (lane == 0) {
            const char* vbase = reinterpret_cast<const char*>(vc) + (size_t)cta * (64 * kChunk);
#pragma unroll 1
            for (int k = 0; k < (live ? 8 : 0); k++) {
                mbar_expect_tx(bar_full + 8 * k, kChunk);
                tma_load_2d(sb + OFF_W + k * kChunk, &tm_wq, h * 128, k * 64, bar_full + 8 * k);
            }
            int slot = 1;
            int wslot = 1, waited = 1 - kStages;
            uint32_t wphase = 1;
            const int n_steps = live ? (role ? 132 : 128) : 4;
#pragma unroll 1
            for (int step = live ? 1 : 0; step < n_steps; step++) {
                constexpr unsigned kDryList = 1u | kWoAt << 8 | 128u << 16 | 130u << 24;
                const int c = live ? step : (int)((kDryList >> (8 * step)) & 255);
                if (live) reinterpret_cast<volatile int*>(smem + OFF_CTL)[0] = c;
                int la = reinterpret_cast<volatile int*>(smem + OFF_CTL)[1];
                if (c < kStages || c >= 128) la = kStages;
                while (live && waited <= c - la) {
                    mbar_wait(bar_empty + 8 * wslot, wphase);
                    waited++;
                    if (++wslot == kStages) { wslot = 0; wphase ^= 1; }
                }
                const uint32_t dst = sb + OFF_RING + slot * kChunk;
                if (c < 128) {
                    const char* src = (c < 64) ? kbase + (size_t)c * kChunk : vbase + (size_t)(c - 64) * kChunk;
                    if (live) {
                        mbar_expect_tx(bar_full + 8 * ((c + 8) & 15), kChunk);
                        bulk_load_pol(dst, src, kChunk, bar_full + 8 * ((c + 8) & 15), pol);
                    }
                    if (c == 1) {
                        tmap_prefetch(&tm_wo);
                        if (role == 1) { tmap_prefetch(&tm_w1); tmap_prefetch(&tm_w3); }
                        if (role == 2) tmap_prefetch(&tm_w2);
                    }
                    const int k = (c - kWoAt) / kWoStep;
                    if (c >= kWoAt && k < 8 && c == kWoAt + k * kWoStep) {
                        if (live) {
                            if (k == 0) mbar_wait(bar_wfree, 0);
                            mbar_expect_tx(bar_wo + 8 * k, kChunk);
                            tma_load_2d(sb + OFF_W + k * kChunk, &tm_wo, k * 64, h * 128, bar_wo + 8 * k);
                        }
                    }
                } else {
                    const int k = c - 128;
                    if (k == 0 && live) mbar_wait(bar_full + 8 * ((127 + 8) & 15), ((127 + 8) >> 4) & 1);
                    if (role == 1) {
                        if (k == 0 && live) mbar_expect_tx(bar_ffn, 4 * kChunk);
                        if (live) tma_load_2d(dst, (k & 2) ? &tm_w3 : &tm_w1, cta * 32, (k & 1) * 256, bar_ffn);
                    } else if (role == 2) {
                        if (k == 0 && live) mbar_expect_tx(bar_ffn, 7 * 8192);
                        if (live) tma_load_2d(dst, &tm_w2, (cta - kFfn2First) * 16, k * 512, bar_ffn);
                        if (k < 3 && live) tma_load_2d(dst + 8192, &tm_w2, (cta - kFfn2First) * 16, k * 512 + 256, bar_ffn);
                    }
                }
                if (++slot == kStages) slot = 0;
            }
        }
        if (live) return;
        __syncwarp();
    }

    const int g = lane >> 2, t = lane & 3;
    const int set = warp >> 2;
    const int grp = warp & 3;
    uint32_t mask[8];
    {
        const int dd = (g - 2 * t) & 7;
#pragma unroll
        for (int j = 0; j < 8; j++)
            mask[j] = (j == dd ? 0x0000ffffu : 0u) | (j == ((dd - 1) & 7) ? 0xffff0000u : 0u);
    }
    const uint32_t vrow = sb + OFF_RING + grp * 4096 + ((lane & 7) + (lane >> 4) * 8) * 256 + ((lane >> 3) & 1) * 128;
    const uint32_t krow = sb + OFF_RING + grp * 4096 + ((lane & 7) + ((lane >> 3) & 1) * 8) * 256 + (lane >> 4) * 128;
    unsigned char* const srow = smem + OFF_S + warp * kSPitch;
    const bool diag = (t == (g >> 1));
    const bool godd = (g & 1) != 0;

    const int nit = live ? 16 : 1;
    unsigned epoch = 0;
    if (live) asm volatile("ld.relaxed.gpu.global.u32 %0, [%1];" : "=r"(epoch) : "l"(&g_epoch) : "memory");
    {
        if (live) mbar_wait(bar_x, 0);
        const uint4 xa = reinterpret_cast<const uint4*>(smem + OFF_X)[2 * lane];
        const uint4 xb = reinterpret_cast<const uint4*>(smem + OFF_X)[2 * lane + 1];
        float xv[16];
        xv[0] = bf_lo(xa.x); xv[1] = bf_hi(xa.x); xv[2] = bf_lo(xa.y); xv[3] = bf_hi(xa.y);
        xv[4] = bf_lo(xa.z); xv[5] = bf_hi(xa.z); xv[6] = bf_lo(xa.w); xv[7] = bf_hi(xa.w);
        xv[8] = bf_lo(xb.x); xv[9] = bf_hi(xb.x); xv[10] = bf_lo(xb.y); xv[11] = bf_hi(xb.y);
        xv[12] = bf_lo(xb.z); xv[13] = bf_hi(xb.z); xv[14] = bf_lo(xb.w); xv[15] = bf_hi(xb.w);
        float s = 0.f;
#pragma unroll
        for (int i = 0; i < 16; i++) s += xv[i];
        const float mean = warp_sum(s) * (1.f / kD);
        float v = 0.f;
#pragma unroll
        for (int i = 0; i < 16; i++) { const float d = xv[i] - mean; v += d * d; }
        const float var = warp_sum(v) * (1.f / kD);
        const float den = bf16r(sqrtf(bf16r(bf16r(var) + 1e-5f)));
        const float mb = bf16r(mean);
        uint32_t xn[4];
#pragma unroll
        for (int k = 0; k < 4; k++) {
            const uint32_t u = reinterpret_cast<const uint32_t*>(smem + OFF_X)[(set + 4 * (k >> 1)) * 32 + grp * 8 + t + (k & 1) * 4];
            xn[k] = pack_bf16(bf16r(bf_lo(u) - mb) / den, bf16r(bf_hi(u) - mb) / den);
        }
        float c0[4] = {0.f, 0.f, 0.f, 0.f}, c1[4] = {0.f, 0.f, 0.f, 0.f};
#pragma unroll 1
        for (int k = 0; k < 2; k++) {
            const int sl = 4 * k + set;
            const uint32_t pp0 = k ? xn[2] : xn[0], pp1 = k ? xn[3] : xn[1];
            if (live) mbar_wait(bar_full + 8 * sl, 0);
#pragma unroll
            for (int j = 0; j < 8; j += 2) {
                uint32_t a0[4], a1[4];
                ldsm4t(a0, vrow + OFF_W + sl * kChunk + ((lane + j) & 7) * 16);
                ldsm4t(a1, vrow + OFF_W + sl * kChunk + ((lane + j + 1) & 7) * 16);
                mma16816(c0, a0, pp0 & mask[j], pp1 & mask[j]);
                mma16816(c1, a1, pp0 & mask[j + 1], pp1 & mask[j + 1]);
            }
        }
        if (lane == 0 && live) mbar_arrive(bar_wfree + ((__float_as_uint(c0[0]) ^ __float_as_uint(c1[0])) & zero));
        float* qp = reinterpret_cast<float*>(srow);
        if (live) {
            qp[(2 * t) * 8 + g] = c0[0] + c1[0];
            qp[(2 * t + 1) * 8 + g] = c0[1] + c1[1];
            qp[(2 * t + 8) * 8 + g] = c0[2] + c1[2];
            qp[(2 * t + 9) * 8 + g] = c0[3] + c1[3];
        }
        bar_cons();
        if (tid < 128) {
            const float* qs = reinterpret_cast<const float*>(smem + OFF_S) + tid;
            float q = 0.f;
#pragma unroll
            for (int w = 0; w < 16; w++) q += qs[w * (kSPitch / 4)];
            if (live) reinterpret_cast<__nv_bfloat16*>(smem + OFF_Q)[tid] = __float2bfloat16_rn(q);
        }
        bar_cons();
    }
    int sl = set;
    {
        uint32_t bq0[8], bq1[8];
        const uint32_t* q2 = reinterpret_cast<const uint32_t*>(smem + OFF_Q);
#pragma unroll
        for (int j = 0; j < 8; j++) {
            bq0[j] = q2[((g + j) & 7) * 4 + t];
            bq1[j] = q2[32 + ((g + j) & 7) * 4 + t];
        }
        float* sc = reinterpret_cast<float*>(srow);
        float mx = -INFINITY;
#pragma unroll 1
        for (int it = 0; it < nit; it++) {
            const int n = it + 2;
            if (live) mbar_wait(bar_full + 8 * ((n & 3) * 4 + set), (n >> 2) & 1);
            float c0[4] = {0.f, 0.f, 0.f, 0.f}, c1[4] = {0.f, 0.f, 0.f, 0.f};
#pragma unroll
            for (int j = 0; j < 8; j += 2) {
                uint32_t a0[4], a1[4];
                ldsm4(a0, krow + sl * kChunk + ((lane + j) & 7) * 16);
                ldsm4(a1, krow + sl * kChunk + ((lane + j + 1) & 7) * 16);
                mma16816(c0, a0, bq0[j], bq1[j]);
                mma16816(c1, a1, bq0[j + 1], bq1[j + 1]);
            }
            if (lane == 0 && live) mbar_arrive(bar_empty + 8 * sl + ((__float_as_uint(c0[0]) ^ __float_as_uint(c1[0])) & zero));
            const float slo = bf16r(bf16r(godd ? c0[1] + c1[1] : c0[0] + c1[0]) * 0.08838834764831845f);
            const float shi = bf16r(bf16r(godd ? c0[3] + c1[3] : c0[2] + c1[2]) * 0.08838834764831845f);
            if (diag && live) {
                sc[it * 16 + g] = slo;
                sc[it * 16 + g + 8] = shi;
                mx = fmaxf(mx, fmaxf(slo, shi));
            }
            sl += 4;
            if (sl >= kStages) sl -= kStages;
        }
        float* smax = reinterpret_cast<float*>(smem + OFF_STAT);
        float* ssum = smax + 16;
        mx = warp_max(mx);
        if (lane == 0 && live) smax[warp] = mx;
        bar_cons();
        {
            const float4* p4 = reinterpret_cast<const float4*>(smax);
            const float4 m0 = p4[0], m1 = p4[1], m2 = p4[2], m3 = p4[3];
            mx = fmaxf(fmaxf(fmaxf(m0.x, m0.y), fmaxf(m0.z, m0.w)), fmaxf(fmaxf(m1.x, m1.y), fmaxf(m1.z, m1.w)));
            mx = fmaxf(mx, fmaxf(fmaxf(fmaxf(m2.x, m2.y), fmaxf(m2.z, m2.w)), fmaxf(fmaxf(m3.x, m3.y), fmaxf(m3.z, m3.w))));
        }
        const float cs = 1.4426950408889634f;
        const float4 s0 = reinterpret_cast<const float4*>(sc)[2 * lane], s1 = reinterpret_cast<const float4*>(sc)[2 * lane + 1];
        float e[8] = {s0.x, s0.y, s0.z, s0.w, s1.x, s1.y, s1.z, s1.w};
        float sum = 0.f;
#pragma unroll
        for (int i = 0; i < 8; i++) { e[i] = exp2f((e[i] - mx) * cs); sum += e[i]; }
        sum = warp_sum(sum);
        if (lane == 0 && live) ssum[warp] = sum;
        bar_cons();
        {
            const float4* p4 = reinterpret_cast<const float4*>(ssum);
            const float4 m0 = p4[0], m1 = p4[1], m2 = p4[2], m3 = p4[3];
            sum = ((m0.x + m0.y) + (m0.z + m0.w)) + ((m1.x + m1.y) + (m1.z + m1.w)) +
                  ((m2.x + m2.y) + (m2.z + m2.w)) + ((m3.x + m3.y) + (m3.z + m3.w));
        }
        const float inv = 1.f / sum;
        if (live) reinterpret_cast<uint4*>(srow + 512)[lane] =
            make_uint4(pack_bf16(e[0] * inv, e[1] * inv), pack_bf16(e[2] * inv, e[3] * inv),
                       pack_bf16(e[4] * inv, e[5] * inv), pack_bf16(e[6] * inv, e[7] * inv));
        __syncwarp();
    }
    const int par = epoch & 1;
    const unsigned tag = epoch + 1;
    if (live) {
        if (tid < 16) g_acc[par ^ 1][cta * 16 + tid] = make_float2(0.f, 0.f);
    }
    float oc[4];
    uint32_t wf[8][2][4];
    const int r8 = lane & 7;
    const uint32_t wbase = sb + OFF_W + (warp >> 1) * kChunk + (r8 + (lane >> 4) * 8) * 128;
    const int cu = (warp & 1) * 4 + ((lane >> 3) & 1);
    {
        const uint32_t* pw = reinterpret_cast<const uint32_t*>(srow + 512) + t;
        float c0[4] = {0.f, 0.f, 0.f, 0.f}, c1[4] = {0.f, 0.f, 0.f, 0.f};
#pragma unroll 1
        for (int it = 0; it < nit; it++) {
            const int n = it + 18;
            const uint32_t pp0 = pw[it * 8], pp1 = pw[it * 8 + 4];
            if (it == nit - 1) {
                if (live) mbar_wait(bar_wo + 8 * (warp >> 1), 0);
#pragma unroll
                for (int s = 0; s < kWfPre; s++) {
                    ldsm4t(wf[s][0], wbase + s * 2048 + ((cu ^ r8) * 16));
                    ldsm4t(wf[s][1], wbase + s * 2048 + (((cu + 2) ^ r8) * 16));
                }
            }
            if (live) mbar_wait(bar_full + 8 * ((n & 3) * 4 + set), (n >> 2) & 1);
#pragma unroll
            for (int j = 0; j < 8; j += 2) {
                uint32_t a0[4], a1[4];
                ldsm4t(a0, vrow + sl * kChunk + ((lane + j) & 7) * 16);
                ldsm4t(a1, vrow + sl * kChunk + ((lane + j + 1) & 7) * 16);
                mma16816(c0, a0, pp0 & mask[j], pp1 & mask[j]);
                mma16816(c1, a1, pp0 & mask[j + 1], pp1 & mask[j + 1]);
            }
            if (lane == 0 && live) mbar_arrive(bar_empty + 8 * sl + ((__float_as_uint(c0[0]) ^ __float_as_uint(c1[0])) & zero));
            sl += 4;
            if (sl >= kStages) sl -= kStages;
        }
#pragma unroll
        for (int k = 0; k < 4; k++) oc[k] = c0[k] + c1[k];
    }
    {
        if (warp >= 8) {
            if (live) {
                reinterpret_cast<float4*>(srow)[lane] = make_float4(oc[0], oc[1], oc[2], oc[3]);
                asm volatile("bar.arrive %0, 64;" ::"r"(2 + (warp & 7)) : "memory");
            }
        }
#pragma unroll
        for (int s = kWfPre; s < 8; s++) {
            ldsm4t(wf[s][0], wbase + s * 2048 + ((cu ^ r8) * 16));
            ldsm4t(wf[s][1], wbase + s * 2048 + (((cu + 2) ^ r8) * 16));
        }
        if (warp < 8) {
            if (live) asm volatile("bar.sync %0, 64;" ::"r"(2 + warp) : "memory");
            const float4 o2 = reinterpret_cast<const float4*>(srow + 8 * kSPitch)[lane];
            __nv_bfloat16* op = reinterpret_cast<__nv_bfloat16*>(srow);
            if (live) {
                op[(2 * t) * 8 + g] = __float2bfloat16_rn(oc[0] + o2.x);
                op[(2 * t + 1) * 8 + g] = __float2bfloat16_rn(oc[1] + o2.y);
                op[(2 * t + 8) * 8 + g] = __float2bfloat16_rn(oc[2] + o2.z);
                op[(2 * t + 9) * 8 + g] = __float2bfloat16_rn(oc[3] + o2.w);
            }
        }
        bar_cons();
        float acc[4][4];
#pragma unroll
        for (int a = 0; a < 4; a++)
#pragma unroll
            for (int k = 0; k < 4; k++) acc[a][k] = 0.f;
        const uint32_t brow = sb + OFF_S + (lane & 7) * kSPitch + (lane >> 3) * 16;
#pragma unroll
        for (int s2 = 0; s2 < 4; s2++) {
            uint32_t bA[4];
            ldsm4(bA, brow + s2 * 64);
            mma16816(acc[0], wf[s2 * 2][0], bA[0], bA[1]);
            mma16816(acc[2], wf[s2 * 2][1], bA[0], bA[1]);
            mma16816(acc[1], wf[s2 * 2 + 1][0], bA[2], bA[3]);
            mma16816(acc[3], wf[s2 * 2 + 1][1], bA[2], bA[3]);
        }
        const float v0 = (acc[0][0] + acc[0][1]) + (acc[1][0] + acc[1][1]);
        const float v1 = (acc[0][2] + acc[0][3]) + (acc[1][2] + acc[1][3]);
        const float v2 = (acc[2][0] + acc[2][1]) + (acc[3][0] + acc[3][1]);
        const float v3 = (acc[2][2] + acc[2][3]) + (acc[3][2] + acc[3][3]);
        const bool o1 = (t & 1) != 0, o2 = (t & 2) != 0;
        const float ra = (o1 ? v1 : v0) + __shfl_xor_sync(0xffffffffu, o1 ? v0 : v1, 1);
        const float rb = (o1 ? v3 : v2) + __shfl_xor_sync(0xffffffffu, o1 ? v2 : v3, 1);
        const float r = (o2 ? rb : ra) + __shfl_xor_sync(0xffffffffu, o2 ? ra : rb, 2);
        if (live) {
            red_add_f2(&g_acc[par][b * kD + warp * 32 + (t >> 1) * 16 + (t & 1) * 8 + g], r, 1.0f);
        }
    }
    if (role == 0) {
        if (!live) goto monitor;
        return;
    }
    {

    uint32_t af[8][4];
    const int rr = (lane & 7) + (lane >> 4) * 8, cc = (lane >> 3) & 1;
    constexpr uint32_t off_hs = OFF_HS, off_part = OFF_PART;
    float* part = reinterpret_cast<float*>(smem + off_part);

    if (role == 1) {
        const int bb = tid >> 7, c4 = (tid & 127) * 4;
        uint2 xr = make_uint2(0u, 0u);
        if (live) asm volatile("ld.global.nc.v2.u32 {%0,%1}, [%2];" : "=r"(xr.x), "=r"(xr.y) : "l"(x + bb * kD + c4));
        if (tid < 64 && live) reinterpret_cast<uint4*>(smem + off_hs + 4 * 1040)[tid] = make_uint4(0x3f803f80u, 0x3f803f80u, 0x3f803f80u, 0x3f803f80u);
        const float4* src = reinterpret_cast<const float4*>(&g_acc[par][bb * kD + c4]);
        float4 u0 = make_float4(0.f, 0.f, 0.f, 0.f), u1 = u0;
        uint32_t tries = 0;
        {
            while (live && lane == 0) {
                const float2 u = ld_relaxed_f2(src);
                if (u.y == 32.f) break;
                if (++tries > kSpinLimit) __trap();
            }
            __syncwarp();
        }
        while (live) {
            u0 = ld_relaxed_f4(src);
            u1 = ld_relaxed_f4(src + 1);
            if (u0.y == 32.f && u0.w == 32.f && u1.y == 32.f && u1.w == 32.f) break;
            if (++tries > kSpinLimit) __trap();
        }
        const uint32_t x0 = xr.x, x1 = xr.y;
        const float h0 = bf16r(bf_lo(x0) + bf16r(u0.x)), h1 = bf16r(bf_hi(x0) + bf16r(u0.z));
        const float h2 = bf16r(bf_lo(x1) + bf16r(u1.x)), h3 = bf16r(bf_hi(x1) + bf16r(u1.z));
        if (live) *reinterpret_cast<uint2*>(smem + off_hs + bb * 1040 + c4 * 2) = make_uint2(pack_bf16(h0, h1), pack_bf16(h2, h3));
        const int kq = warp >> 2;
        if (live) mbar_wait(bar_ffn, 0);
        {
            const uint32_t box = sb + OFF_RING + slot_at(128, (warp & 2) + (kq >> 1)) * kChunk;
#pragma unroll
            for (int s = 0; s < 8; s++) {
                const int r = (kq & 1) * 128 + s * 16 + rr;
                ldsm4t(af[s], box + r * 64 + ((((warp & 1) * 2 + cc) ^ ((r >> 1) & 3)) * 16));
            }
        }
        bar_cons();
        float c0[4] = {0.f, 0.f, 0.f, 0.f}, c1[4] = {0.f, 0.f, 0.f, 0.f};
        float q0[4] = {0.f, 0.f, 0.f, 0.f}, q1[4] = {0.f, 0.f, 0.f, 0.f};
        const uint32_t brow = sb + off_hs + min(lane & 7, 4) * 1040 + (kq * 128 + (lane >> 3) * 8) * 2;
        const bool statw = (warp & 3) == kq;
#pragma unroll
        for (int s2 = 0; s2 < 4; s2++) {
            uint32_t bf[4];
            ldsm4(bf, brow + s2 * 64);
            mma16816(c0, af[2 * s2], bf[0], bf[1]);
            mma16816(c1, af[2 * s2 + 1], bf[2], bf[3]);
            if (statw) {
                const uint32_t a0[4] = {bf[0], 0u, bf[1], 0u}, a1[4] = {bf[2], 0u, bf[3], 0u};
                mma16816(q0, a0, bf[0], bf[1]);
                mma16816(q1, a1, bf[2], bf[3]);
            }
        }
        if (t < 3 && live) {
            float* pw = part + ((warp & 3) * 16 + g) * 28 + t * 8 + kq;
            pw[0] = c0[0] + c1[0]; pw[4] = c0[1] + c1[1];
            pw[224] = c0[2] + c1[2]; pw[228] = c0[3] + c1[3];
            if (statw) { float* ps = part + (64 + g) * 28 + t * 8 + kq; ps[0] = q0[0] + q1[0]; ps[4] = q0[1] + q1[1]; }
        }
        bar_cons();
        if (tid < 128) {
            const int eb = tid & 3, fl = tid >> 2, tile = fl >> 4, m = fl & 15;
            const float4* p4 = reinterpret_cast<const float4*>(part);
            const float4 vg = p4[(tile * 16 + m) * 7 + eb], vgs = p4[(tile * 16 + m) * 7 + 4];
            const float4 vu = p4[((tile + 2) * 16 + m) * 7 + eb], vus = p4[((tile + 2) * 16 + m) * 7 + 4];
            const float4 vq = p4[(64 + eb) * 7 + eb], vs = p4[(64 + 4) * 7 + eb];
            const float gr = (vg.x + vg.y) + (vg.z + vg.w), gs = (vgs.x + vgs.y) + (vgs.z + vgs.w);
            const float ur = (vu.x + vu.y) + (vu.z + vu.w), us = (vus.x + vus.y) + (vus.z + vus.w);
            const float mean = ((vs.x + vs.y) + (vs.z + vs.w)) * (1.f / kD);
            const float var = fmaxf(((vq.x + vq.y) + (vq.z + vq.w)) * (1.f / kD) - mean * mean, 0.f);
            float sq, rden;
            asm("sqrt.approx.f32 %0, %1;" : "=f"(sq) : "f"(bf16r(bf16r(var) + 1e-5f)));
            asm("rcp.approx.f32 %0, %1;" : "=f"(rden) : "f"(bf16r(sq)));
            const float mb = bf16r(mean);
            const float gate = bf16r((gr - mb * gs) * rden);
            const float up = bf16r((ur - mb * us) * rden);
            const float act = bf16r(__fdividef(gate, 1.f + __expf(-gate)));
            const float hh = bf16r(act * up);
            const float hn = __shfl_xor_sync(0xffffffffu, hh, 4);
            if ((fl & 1) == 0 && live) {
                const int ks = cta * 2 + tile;
                const uint32_t pk = pack_bf16(hh, hn);
                st_relaxed_64(reinterpret_cast<char*>(&g_ll[(ks * 4 + eb) * 4 + ((m & 7) >> 1)]) + (m >> 3) * 8, pk, tag);
            }
        }
    } else {
        const int c0col = (cta - kFfn2First) * 16;
        float hres = 0.f;
        const int oo = tid >> 2, om = oo >> 2, ob = oo & 3;
        {
            uint32_t tries = 0;
            while (live) {
                bool ok = true;
                if (lane < 4) ok = ld_relaxed_f2(&g_acc[par][lane * kD + c0col + (warp & 15)]).y == 32.f;
                if (__all_sync(0xffffffffu, ok)) break;
                if (++tries > kSpinLimit) __trap();
            }
        }
        if (tid < 256 && (tid & 3) == 0 && live) {
            const float xv = __bfloat162float(x[ob * kD + c0col + om]);
            float2 u;
            uint32_t tries = 0;
            while (true) {
                u = ld_relaxed_f2(&g_acc[par][ob * kD + c0col + om]);
                if (u.y == 32.f) break;
                if (++tries > kSpinLimit) __trap();
            }
            hres = bf16r(xv + bf16r(u.x));
        }
        if (live) mbar_wait(bar_ffn, 0);
#pragma unroll
        for (int s = 0; s < 7; s++) {
            const int f = warp * 112 + s * 16 + rr;
            const uint32_t box = sb + OFF_RING + slot_at(128, f >> 9) * kChunk;
            ldsm4t(af[s], box + (f & 511) * 32 + ((cc ^ ((f >> 2) & 1)) * 16));
        }
        uint4 ll[7];
#pragma unroll
        for (int s = 0; s < 7; s++) ll[s] = make_uint4(0u, 0u, 0u, 0u);
        const uint4* lsrc = &g_ll[(warp * 7 * 4 + (g & 3)) * 4 + t];
        uint32_t tries = 0;
        while (live) {
            bool ok = true;
#pragma unroll
            for (int s = 0; s < 7; s++) ll[s] = ld_relaxed_2x64(lsrc + s * 16);
#pragma unroll
            for (int s = 0; s < 7; s++) ok = ok && (ll[s].y == tag) && (ll[s].w == tag);
            if (__all_sync(0xffffffffu, ok)) break;
            if (++tries > kSpinLimit) __trap();
        }
        float c0[4] = {0.f, 0.f, 0.f, 0.f}, c1[4] = {0.f, 0.f, 0.f, 0.f};
#pragma unroll
        for (int s = 0; s < 7; s++) {
            if (s & 1) mma16816(c1, af[s], ll[s].x, ll[s].z);
            else mma16816(c0, af[s], ll[s].x, ll[s].z);
        }
        if (t < 2 && live) {
            float* pw = part + (g * 4 + 2 * t) * 16 + warp;
            pw[0] = c0[0] + c1[0]; pw[16] = c0[1] + c1[1];
            pw[512] = c0[2] + c1[2]; pw[528] = c0[3] + c1[3];
        }
        bar_cons();
        if (tid < 256) {
            const int qq = tid & 3;
            const float4 pv = reinterpret_cast<const float4*>(part)[tid];
            float s = (pv.x + pv.y) + (pv.z + pv.w);
            s += __shfl_xor_sync(0xffffffffu, s, 1);
            s += __shfl_xor_sync(0xffffffffu, s, 2);
            if (qq == 0 && live) out[ob * kD + c0col + om] = __float2bfloat16_rn(hres + bf16r(s));
        }
        if (cta == kFfn2First && tid == 0 && live) g_epoch = epoch + 1;
    }
    }
monitor:
    if (threadIdx.x == 544) {
        unsigned ep;
        asm volatile("ld.relaxed.gpu.global.u32 %0, [%1];" : "=r"(ep) : "l"(&g_epoch) : "memory");
        unsigned* pp = &g_prog[ep & 1];
        if (cta == 0) g_prog[(ep & 1) ^ 1] = 0;
        int last = 0;
        for (uint32_t tries = 0; tries < kSpinLimit; tries++) {
            const int my = reinterpret_cast<volatile int*>(smem + OFF_CTL)[0];
            unsigned tot;
            asm volatile("atom.relaxed.gpu.global.add.u32 %0, [%1], %2;" : "=r"(tot) : "l"(pp), "r"(my - last) : "memory");
            tot += my - last;
            last = my;
            if (my >= 127) break;
            const int diff = my * 128 - (int)tot;
            reinterpret_cast<volatile int*>(smem + OFF_CTL)[1] = diff < 0 ? kStages : kLookahead;
            __nanosleep(300);
        }
    }
}

__device__ float f_q[4 * kHD], f_o[4 * kHD], f_h[4 * kD], f_hh[4 * kF];

DEVINL float block_sum(float v, float* red) {
    v = warp_sum(v);
    __syncthreads();
    if ((threadIdx.x & 31) == 0) red[threadIdx.x >> 5] = v;
    __syncthreads();
    float s = 0.f;
    for (int i = 0; i < (int)(blockDim.x >> 5); i++) s += red[i];
    return s;
}
DEVINL void ln512(float v0, float v1, float* xn, float* red) {
    const float mean = block_sum(v0 + v1, red) * (1.f / kD);
    const float var = block_sum((v0 - mean) * (v0 - mean) + (v1 - mean) * (v1 - mean), red) * (1.f / kD);
    const float den = bf16r(sqrtf(bf16r(bf16r(var) + 1e-5f))), mb = bf16r(mean);
    xn[threadIdx.x] = bf16r(bf16r(v0 - mb) / den);
    xn[threadIdx.x + 256] = bf16r(bf16r(v1 - mb) / den);
    __syncthreads();
}
__global__ void fb_q(const __nv_bfloat16* x, const __nv_bfloat16* wq) {
    __shared__ float xn[kD], red[8];
    const int b = blockIdx.y, c = blockIdx.x * 256 + threadIdx.x;
    ln512(__bfloat162float(x[b * kD + threadIdx.x]), __bfloat162float(x[b * kD + threadIdx.x + 256]), xn, red);
    float a = 0.f;
    for (int i = 0; i < kD; i++) a = fmaf(xn[i], __bfloat162float(wq[(size_t)i * kHD + c]), a);
    f_q[b * kHD + c] = bf16r(a);
}
__global__ void fb_attn(const __nv_bfloat16* kc, const __nv_bfloat16* vc) {
    __shared__ float sc[4096], red[8], q[128];
    const int bh = blockIdx.x, tid = threadIdx.x;
    if (tid < 128) q[tid] = f_q[bh * 128 + tid];
    __syncthreads();
    float mx = -INFINITY;
    for (int k = tid; k < 4096; k += 256) {
        const __nv_bfloat16* kr = kc + ((size_t)bh * 4096 + k) * 128;
        float a = 0.f;
        for (int d = 0; d < 128; d++) a = fmaf(q[d], __bfloat162float(kr[d]), a);
        a = bf16r(bf16r(a) * 0.08838834764831845f);
        sc[k] = a;
        mx = fmaxf(mx, a);
    }
    mx = warp_max(mx);
    if ((tid & 31) == 0) red[tid >> 5] = mx;
    __syncthreads();
    for (int i = 0; i < 8; i++) mx = fmaxf(mx, red[i]);
    float l = 0.f;
    for (int k = tid; k < 4096; k += 256) { sc[k] = expf(sc[k] - mx); l += sc[k]; }
    l = block_sum(l, red);
    if (tid < 128) {
        float a = 0.f;
        for (int k = 0; k < 4096; k++) a = fmaf(bf16r(sc[k] / l), __bfloat162float(vc[((size_t)bh * 4096 + k) * 128 + tid]), a);
        f_o[bh * 128 + tid] = bf16r(a);
    }
}
__global__ void fb_wo(const __nv_bfloat16* x, const __nv_bfloat16* wo) {
    const int b = blockIdx.x, c = threadIdx.x;
    float a = 0.f;
    for (int i = 0; i < kHD; i++) a = fmaf(f_o[b * kHD + i], __bfloat162float(wo[(size_t)i * kD + c]), a);
    f_h[b * kD + c] = bf16r(__bfloat162float(x[b * kD + c]) + bf16r(a));
}
__global__ void fb_ffn1(const __nv_bfloat16* w1, const __nv_bfloat16* w3) {
    __shared__ float xn[kD], red[8];
    const int b = blockIdx.y, c = blockIdx.x * 256 + threadIdx.x;
    ln512(f_h[b * kD + threadIdx.x], f_h[b * kD + threadIdx.x + 256], xn, red);
    float g = 0.f, u = 0.f;
    for (int i = 0; i < kD; i++) {
        g = fmaf(xn[i], __bfloat162float(w1[(size_t)i * kF + c]), g);
        u = fmaf(xn[i], __bfloat162float(w3[(size_t)i * kF + c]), u);
    }
    g = bf16r(g);
    f_hh[b * kF + c] = bf16r(bf16r(g / (1.f + expf(-g))) * bf16r(u));
}
__global__ void fb_ffn2(const __nv_bfloat16* w2, __nv_bfloat16* out) {
    const int b = blockIdx.x, c = threadIdx.x;
    float a = 0.f;
    for (int i = 0; i < kF; i++) a = fmaf(f_hh[b * kF + i], __bfloat162float(w2[(size_t)i * kD + c]), a);
    out[b * kD + c] = __float2bfloat16_rn(f_h[b * kD + c] + bf16r(a));
}

typedef CUresult (*EncodeFn)(CUtensorMap*, CUtensorMapDataType, cuuint32_t, void*, const cuuint64_t*, const cuuint64_t*,
                             const cuuint32_t*, const cuuint32_t*, CUtensorMapInterleave, CUtensorMapSwizzle,
                             CUtensorMapL2promotion, CUtensorMapFloatOOBfill);

static void make_map(EncodeFn enc, CUtensorMap* m, void* ptr, uint64_t cols, uint64_t rows, uint32_t bc, uint32_t br,
                     CUtensorMapSwizzle sw) {
    cuuint64_t dims[2] = {cols, rows};
    cuuint64_t strides[1] = {cols * 2};
    cuuint32_t box[2] = {bc, br};
    cuuint32_t es[2] = {1, 1};
    enc(m, CU_TENSOR_MAP_DATA_TYPE_BFLOAT16, 2, ptr, dims, strides, box, es, CU_TENSOR_MAP_INTERLEAVE_NONE, sw,
        CU_TENSOR_MAP_L2_PROMOTION_L2_128B, CU_TENSOR_MAP_FLOAT_OOB_FILL_NONE);
}

}

extern "C" void kernel_launch(void* const* d_in, const int* in_sizes, int n_in, void* d_out, int out_size) {
    (void)in_sizes; (void)n_in; (void)out_size;
    using namespace fused;
    typedef const __nv_bfloat16* P;
    static int mode = -1;
    static EncodeFn enc = nullptr;
    if (mode < 0) {
        void* fn = nullptr;
        cudaDriverEntryPointQueryResult st;
        cudaGetDriverEntryPoint("cuTensorMapEncodeTiled", &fn, cudaEnableDefault, &st);
        enc = (EncodeFn)fn;
        int dev = 0, sms = 0, per_sm = 0;
        cudaGetDevice(&dev);
        cudaDeviceGetAttribute(&sms, cudaDevAttrMultiProcessorCount, dev);
        const cudaError_t e = cudaFuncSetAttribute(fused_kernel, cudaFuncAttributeMaxDynamicSharedMemorySize, SMEM_BYTES);
        if (e == cudaSuccess) cudaOccupancyMaxActiveBlocksPerMultiprocessor(&per_sm, fused_kernel, kThreads, SMEM_BYTES);
        (void)cudaGetLastError();
        mode = (enc != nullptr && e == cudaSuccess && sms * per_sm >= kCtas) ? 1 : 0;
    }
    if (mode == 0) {
        fb_q<<<dim3(16, 4), 256>>>((P)d_in[0], (P)d_in[3]);
        fb_attn<<<128, 256>>>((P)d_in[1], (P)d_in[2]);
        fb_wo<<<4, 512>>>((P)d_in[0], (P)d_in[4]);
        fb_ffn1<<<dim3(7, 4), 256>>>((P)d_in[6], (P)d_in[7]);
        fb_ffn2<<<4, 512>>>((P)d_in[8], (__nv_bfloat16*)d_out);
        return;
    }
    CUtensorMap mq, mo, m1, m3, m2;
    make_map(enc, &mq, d_in[3], kHD, kD, 128, 64, CU_TENSOR_MAP_SWIZZLE_NONE);
    make_map(enc, &mo, d_in[4], kD, kHD, 64, 128, CU_TENSOR_MAP_SWIZZLE_128B);
    make_map(enc, &m1, d_in[6], kF, kD, 32, 256, CU_TENSOR_MAP_SWIZZLE_64B);
    make_map(enc, &m3, d_in[7], kF, kD, 32, 256, CU_TENSOR_MAP_SWIZZLE_64B);
    make_map(enc, &m2, d_in[8], kD, kF, 16, 256, CU_TENSOR_MAP_SWIZZLE_32B);
    fused_kernel<<<kCtas, kThreads, SMEM_BYTES>>>(mq, mo, m1, m3, m2, (P)d_in[0], (P)d_in[1], (P)d_in[2],
                                                  (__nv_bfloat16*)d_out, 0u);
}
```
